```python
import torch

def _softmax(x, axis=-1):
    return torch.softmax(x, dim=axis)

def _gelu(x):
    return torch.nn.functional.gelu(x, approximate='tanh')

def _silu(x):
    return torch.nn.functional.silu(x)

def _sigmoid(x):
    return torch.sigmoid(x)

def _layernorm(x, axis=-1, eps=1e-05):
    m = x.mean(dim=axis, keepdim=True)
    v = x.var(dim=axis, keepdim=True, unbiased=False)
    return (x - m) / torch.sqrt(v + eps)

def _scatter_add(tgt, idx, src, axis=0):
    return tgt.clone().index_add_(axis, idx, src)

def _segment_sum(src, seg, n):
    out = torch.zeros((n,) + src.shape[1:], dtype=src.dtype)
    return out.index_add_(0, seg, src)

def _pad(x, pw):
    flat = tuple((v for pair in reversed(pw) for v in pair))
    return torch.nn.functional.pad(x, flat)
kernel_name = 'parallel_sum__sliding_local_dilated__mixer_gmlp__prompt'

def setup_inputs():

    _w = lambda a: (lambda t: t.to(torch.bfloat16) if t.is_floating_point() else t)(torch.as_tensor(a))

    def _A_setup():
        B, S, D = (1, 2048, 448)
        return {'x': _w((lambda *s: torch.randn(*s, dtype=torch.bfloat16) * 0.05)(B, S, D)), 'wqkv': _w((lambda *s: torch.randn(*s, dtype=torch.bfloat16) * 0.1)(D, 3 * D)), 'wo': _w((lambda *s: torch.randn(*s, dtype=torch.bfloat16) * 0.05)(D, D))}
    _A_in = _A_setup()

    def _B_setup():
        B, S, D, F = (1, 2048, 448, 1792)
        Fh = F // 2
        return {'x': _w((lambda *s: torch.randn(*s, dtype=torch.bfloat16) * 0.05)(B, S, D)), 'w_in': _w((lambda *s: torch.randn(*s, dtype=torch.bfloat16) * 0.4)(D, 2 * Fh)), 'w_sp': _w(0.01 * (lambda *s: torch.randn(*s, dtype=torch.bfloat16) * 0.4)(S, S)), 'b_sp': _w(1.0 + 0.01 * (lambda *s: torch.randn(*s, dtype=torch.bfloat16) * 0.05)(S)), 'w_out': _w((lambda *s: torch.randn(*s, dtype=torch.bfloat16) * 0.05)(Fh, D))}
    _B_in = _B_setup()
    return {'A_x': _A_in['x'], 'A_wqkv': _A_in['wqkv'], 'A_wo': _A_in['wo'], 'B_x': _B_in['x'], 'B_w_in': _B_in['w_in'], 'B_w_sp': _B_in['w_sp'], 'B_b_sp': _B_in['b_sp'], 'B_w_out': _B_in['w_out']}

def reference(A_x, A_wqkv, A_wo, B_x, B_w_in, B_w_sp, B_b_sp, B_w_out):

    def _A_ref(x, wqkv, wo):
        B, S, D = x.shape
        H = 16
        Dh = D // H
        W, dil = (8, 2)
        qkv = (lambda x, *d: x.permute(*d))((x @ wqkv).reshape(B, S, 3, H, Dh), 2, 0, 3, 1, 4)
        q, k, v = (qkv[0], qkv[1], qkv[2])
        scale = Dh ** (-0.5)
        pos = torch.arange(S)
        off = torch.arange(W) * dil
        idx = pos[:, None] - off[None, :]
        mask = idx >= 0
        idx_c = torch.where(mask, idx, 0).reshape(-1)
        kg = k[:, :, idx_c, :].reshape(B, H, S, W, Dh)
        vg = v[:, :, idx_c, :].reshape(B, H, S, W, Dh)
        logits = torch.einsum('bhsd,bhswd->bhsw', q, kg) * scale
        logits = torch.where(mask[None, None, :, :], logits, -1000000000.0)
        attn = _softmax(logits, axis=-1)
        o = torch.einsum('bhsw,bhswd->bhsd', attn, vg)
        return (lambda x, *d: x.permute(*d))(o, 0, 2, 1, 3).reshape(B, S, D) @ wo

    def _B_ref(x, w_in, w_sp, b_sp, w_out):
        B, S, D = x.shape
        F = w_in.shape[-1]
        Fh = F // 2
        z = _gelu(torch.einsum('bsd,df->bsf', x, w_in))
        z1 = z[..., :Fh].clone()
        z2 = _layernorm(z[..., Fh:], axis=-1)
        g = torch.einsum('ts,bsf->btf', w_sp, z2) + b_sp[None, :, None]
        return torch.einsum('bsf,fd->bsd', z1 * g, w_out)
    x = A_x
    xn = _layernorm(x, axis=-1)
    return x + _A_ref(xn, A_wqkv, A_wo) + _B_ref(xn, B_w_in, B_w_sp, B_b_sp, B_w_out)
```

```cpp
#include <cuda_runtime.h>
#include <cuda_bf16.h>
#include <cuda.h>
#include <stdint.h>

namespace {

struct Scratch {
  uint4 z2t[32 * 896 * 8];
  uint4 ufrag[128 * 8 * 7 * 32];
  uint4 ofrag[128 * 8 * 112];
  uint4 img[8 * 25088];
  uint2 stats[2048 * 8];
  uint4 halo[128 * 256];
  unsigned cnt_p2[32], cnt_p3[32], cnt_bg[32];
  unsigned cnt_z2[16][32];
  unsigned hint_u[128][32];
  unsigned hint_o[32][32];
  unsigned epoch[128];
};
__device__ __align__(1024) Scratch g_scratch;

constexpr uint32_t STAGE2 = 45056;
constexpr uint32_t BOX1 = 8192;
constexpr uint32_t ZBLK = 14336;
constexpr uint32_t P2ST = 14336, P3ST = 21504;
constexpr uint32_t W3BLK = 25088;
constexpr uint32_t XO_OFF = W3BLK;
constexpr uint32_t OB_OFF = STAGE2 + 32768;
constexpr uint32_t Q_OFF = 4 * STAGE2;
constexpr uint32_t K_OFF = Q_OFF + 128 * 112;
constexpr uint32_t V_OFF = K_OFF + 144 * 112;
constexpr uint32_t BAR_OFF = Q_OFF + 6 * BOX1;
constexpr uint32_t RS_OFF = BAR_OFF + 768;
constexpr uint32_t NB_OFF = BAR_OFF + 1280;
constexpr uint32_t SMEM_BYTES = BAR_OFF + 3072;
constexpr int IMG_P2 = 0, IMG_P3 = 6272, IMG_W3 = 15680, IMG_SZ = 25088;
constexpr int B_P1F = 0, B_P2F = 21, B_P3F = 25, B_GX = 31, B_FX = 33, B_PEERQ = 35, B_ORDY = 36, B_ST = 37,
              B_P1E = 40, B_P2E = 61,
              B_ZFULL = 65, B_QK = 66, B_V = 68, B_XE = 70, B_RP = 71,
              B_XF = 72, B_ZFREE = 74, B_RP2 = 76, B_HK = 77, B_HV = 78,
              B_OF = 79, B_UF = 80, B_SPACE = 86, B_WFREE = 87, B_GFREE = 89, B_COUNT = 91;
constexpr uint32_t CNT_OFF = BAR_OFF + 8 * B_COUNT;

constexpr int XORDER = 3, G0T = 5, SPL = 2, SPL2 = 4, RPS = 5;
constexpr int NPOLL = 2;
constexpr unsigned POLLNS = 100;
constexpr int NSVC = 4, SVE = 5;
constexpr uint32_t SPIN_LIMIT = 1u << 22;

#define TSTAMP(role, idx) do {} while (0)

__device__ __forceinline__ uint32_t smem_u32(const void* p) { return (uint32_t)__cvta_generic_to_shared(p); }
__device__ __forceinline__ void mbar_init(uint32_t bar, uint32_t cnt) { asm volatile("mbarrier.init.shared::cta.b64 [%0], %1;" :: "r"(bar), "r"(cnt) : "memory"); }
__device__ __forceinline__ void mbar_expect_tx(uint32_t bar, uint32_t bytes) { asm volatile("mbarrier.arrive.expect_tx.shared::cta.b64 _, [%0], %1;" :: "r"(bar), "r"(bytes) : "memory"); }
__device__ __forceinline__ void mbar_arrive(uint32_t bar) { asm volatile("mbarrier.arrive.shared::cta.b64 _, [%0];" :: "r"(bar) : "memory"); }
__device__ __forceinline__ void mbar_arrive_remote(uint32_t rbar) { asm volatile("mbarrier.arrive.shared::cluster.b64 _, [%0];" :: "r"(rbar) : "memory"); }
__device__ __forceinline__ void mbar_wait(uint32_t bar, uint32_t parity) {
  asm volatile("{\n.reg .pred p;\nWL:\nmbarrier.try_wait.parity.shared::cta.b64 p, [%0], %1;\n@!p bra WL;\n}\n" :: "r"(bar), "r"(parity) : "memory");
}
__device__ __forceinline__ void mbar_wait_cluster(uint32_t bar, uint32_t parity) {
  asm volatile("{\n.reg .pred p;\nWL:\nmbarrier.try_wait.parity.acquire.cluster.shared::cta.b64 p, [%0], %1;\n@!p bra WL;\n}\n" :: "r"(bar), "r"(parity) : "memory");
}
__device__ __forceinline__ void tma_2d(uint32_t dst, const CUtensorMap* map, int c0, int c1, uint32_t bar) {
  asm volatile("cp.async.bulk.tensor.2d.shared::cluster.global.mbarrier::complete_tx::bytes [%0], [%1, {%3, %4}], [%2];"
    :: "r"(dst), "l"(map), "r"(bar), "r"(c0), "r"(c1) : "memory");
}
__device__ __forceinline__ void tma_3d(uint32_t dst, const CUtensorMap* map, int c0, int c1, int c2, uint32_t bar) {
  asm volatile("cp.async.bulk.tensor.3d.shared::cluster.global.mbarrier::complete_tx::bytes [%0], [%1, {%3, %4, %5}], [%2];"
    :: "r"(dst), "l"(map), "r"(bar), "r"(c0), "r"(c1), "r"(c2) : "memory");
}
__device__ __forceinline__ bool elect_one() {
  uint32_t ok;
  asm volatile("{\n.reg .pred p;\nelect.sync _|p, 0xffffffff;\nselp.u32 %0, 1, 0, p;\n}\n" : "=r"(ok));
  return ok != 0;
}
__device__ __forceinline__ void bulk_g2s(uint32_t dst, const void* src, uint32_t bytes, uint32_t bar) {
  asm volatile("cp.async.bulk.shared::cluster.global.mbarrier::complete_tx::bytes [%0], [%1], %2, [%3];"
    :: "r"(dst), "l"(src), "r"(bytes), "r"(bar) : "memory");
}
__device__ __forceinline__ void bulk_s2g(void* dst, uint32_t src, uint32_t bytes) {
  asm volatile("cp.async.bulk.global.shared::cta.bulk_group [%0], [%1], %2;" :: "l"(dst), "r"(src), "r"(bytes) : "memory");
}
__device__ __forceinline__ void tma_store_2d(const CUtensorMap* map, int c0, int c1, uint32_t src) {
  asm volatile("cp.async.bulk.tensor.2d.global.shared::cta.bulk_group [%0, {%1, %2}], [%3];" :: "l"(map), "r"(c0), "r"(c1), "r"(src) : "memory");
}
__device__ __forceinline__ void l2_prefetch(const void* src, uint32_t bytes) {
  asm volatile("cp.async.bulk.prefetch.L2.global [%0], %1;" :: "l"(src), "r"(bytes) : "memory");
}
__device__ __forceinline__ void wgmma_fence() { asm volatile("wgmma.fence.sync.aligned;" ::: "memory"); }
__device__ __forceinline__ void wgmma_commit() { asm volatile("wgmma.commit_group.sync.aligned;" ::: "memory"); }
template<int N> __device__ __forceinline__ void wgmma_wait() { asm volatile("wgmma.wait_group.sync.aligned %0;" :: "n"(N) : "memory"); }
__device__ __forceinline__ void fence_async_smem() { asm volatile("fence.proxy.async.shared::cta;" ::: "memory"); }
__device__ __forceinline__ void fence_async_global() { asm volatile("fence.proxy.async.global;" ::: "memory"); }
__device__ __forceinline__ void bar_sync(int id, int n) { asm volatile("bar.sync %0, %1;" :: "r"(id), "r"(n) : "memory"); }
__device__ __forceinline__ void bar_arrive(int id, int n) { asm volatile("bar.arrive %0, %1;" :: "r"(id), "r"(n) : "memory"); }
__device__ __forceinline__ uint32_t mapa(uint32_t a, uint32_t cta) { uint32_t r; asm volatile("mapa.shared::cluster.u32 %0, %1, %2;" : "=r"(r) : "r"(a), "r"(cta)); return r; }
__device__ __forceinline__ void st_async_v4(uint32_t raddr, uint32_t a, uint32_t b, uint32_t c, uint32_t d, uint32_t rbar) {
  asm volatile("st.async.weak.shared::cluster.mbarrier::complete_tx::bytes.v4.b32 [%0], {%1,%2,%3,%4}, [%5];" :: "r"(raddr), "r"(a), "r"(b), "r"(c), "r"(d), "r"(rbar) : "memory");
}
__device__ __forceinline__ void st_async_v2(uint32_t raddr, uint32_t a, uint32_t b, uint32_t rbar) {
  asm volatile("st.async.weak.shared::cluster.mbarrier::complete_tx::bytes.v2.b32 [%0], {%1,%2}, [%3];" :: "r"(raddr), "r"(a), "r"(b), "r"(rbar) : "memory");
}
__device__ __forceinline__ void red_release(unsigned* p) { asm volatile("red.release.gpu.global.add.u32 [%0], 1;" :: "l"(p) : "memory"); }
__device__ __forceinline__ void red_relaxed(unsigned* p) { asm volatile("red.relaxed.gpu.global.add.u32 [%0], 1;" :: "l"(p) : "memory"); }
__device__ __forceinline__ void wait_cnt(const unsigned* p, unsigned v) {
  asm volatile("{\n.reg .pred p;\n.reg .u32 n, t;\nmov.u32 n, 0;\nWL:\nld.acquire.gpu.global.u32 t, [%0];\nsetp.eq.u32 p, t, %1;\n@p bra WD;\n"
               "nanosleep.u32 100;\nadd.u32 n, n, 1;\nsetp.lt.u32 p, n, %2;\n@p bra WL;\ntrap;\nWD:\n}\n" :: "l"(p), "r"(v), "n"(SPIN_LIMIT) : "memory");
}
__device__ __forceinline__ unsigned ld_relaxed_32(const unsigned* p) { unsigned v; asm volatile("ld.relaxed.gpu.global.u32 %0, [%1];" : "=r"(v) : "l"(p) : "memory"); return v; }
__device__ __forceinline__ void wait_hint(const unsigned* p, unsigned v) {
  unsigned h[NPOLL], n = 0;
  #pragma unroll
  for (int k = 0; k < NPOLL; k++) { h[k] = ld_relaxed_32(p); __nanosleep(POLLNS); }
  while (true) {
    #pragma unroll
    for (int k = 0; k < NPOLL; k++) { if (h[k] == v) return; h[k] = ld_relaxed_32(p); }
    if (++n > SPIN_LIMIT) __trap();
  }
}
__device__ __forceinline__ void st_relaxed_32(unsigned* p, unsigned v) { asm volatile("st.relaxed.gpu.global.u32 [%0], %1;" :: "l"(p), "r"(v) : "memory"); }
__device__ __forceinline__ bool mbar_test(uint32_t bar, uint32_t parity) {
  uint32_t ok;
  asm volatile("{\n.reg .pred p;\nmbarrier.test_wait.parity.shared::cta.b64 p, [%1], %2;\nselp.u32 %0, 1, 0, p;\n}\n" : "=r"(ok) : "r"(bar), "r"(parity) : "memory");
  return ok != 0;
}
__device__ __forceinline__ unsigned ld_u32_lazy(const unsigned* p) { unsigned v; asm volatile("ld.global.u32 %0, [%1];" : "=r"(v) : "l"(p)); return v; }
__device__ __forceinline__ uint4 ld_nc_v4(const void* p) {
  uint4 v; asm volatile("ld.global.nc.L1::no_allocate.v4.u32 {%0,%1,%2,%3}, [%4];" : "=r"(v.x), "=r"(v.y), "=r"(v.z), "=r"(v.w) : "l"(p)); return v;
}
__device__ __forceinline__ uint4 ld_relaxed_128(const void* p) {
  uint4 v; asm volatile("{\n.reg .b128 t;\nld.relaxed.gpu.global.b128 t, [%4];\nmov.b128 {%0,%1,%2,%3}, t;\n}\n" : "=r"(v.x), "=r"(v.y), "=r"(v.z), "=r"(v.w) : "l"(p) : "memory"); return v;
}
__device__ __forceinline__ void st_relaxed_128(void* p, uint32_t a, uint32_t b, uint32_t c, uint32_t d) {
  asm volatile("{\n.reg .b128 t;\nmov.b128 t, {%1,%2,%3,%4};\nst.relaxed.gpu.global.b128 [%0], t;\n}\n" :: "l"(p), "r"(a), "r"(b), "r"(c), "r"(d) : "memory");
}
__device__ __forceinline__ uint4 ld_relaxed_2x64(const void* p) {
  uint4 v; asm volatile("{\n.reg .b64 a, b;\nld.relaxed.gpu.global.v2.b64 {a, b}, [%4];\nmov.b64 {%0,%1}, a;\nmov.b64 {%2,%3}, b;\n}\n" : "=r"(v.x), "=r"(v.y), "=r"(v.z), "=r"(v.w) : "l"(p) : "memory"); return v;
}
__device__ __forceinline__ void st_relaxed_64(void* p, uint32_t a, uint32_t b) {
  asm volatile("{\n.reg .b64 t;\nmov.b64 t, {%1,%2};\nst.relaxed.gpu.global.b64 [%0], t;\n}\n" :: "l"(p), "r"(a), "r"(b) : "memory");
}
__device__ __forceinline__ uint4 lds_v4(uint32_t a) { uint4 v; asm volatile("ld.shared.v4.u32 {%0,%1,%2,%3}, [%4];" : "=r"(v.x), "=r"(v.y), "=r"(v.z), "=r"(v.w) : "r"(a) : "memory"); return v; }
__device__ __forceinline__ uint2 lds_v2(uint32_t a) { uint2 v; asm volatile("ld.shared.v2.u32 {%0,%1}, [%2];" : "=r"(v.x), "=r"(v.y) : "r"(a) : "memory"); return v; }
__device__ __forceinline__ uint32_t lds_u32(uint32_t a) { uint32_t v; asm volatile("ld.shared.u32 %0, [%1];" : "=r"(v) : "r"(a) : "memory"); return v; }
__device__ __forceinline__ void sts_v4(uint32_t a, uint4 v) { asm volatile("st.shared.v4.u32 [%0], {%1,%2,%3,%4};" :: "r"(a), "r"(v.x), "r"(v.y), "r"(v.z), "r"(v.w) : "memory"); }
__device__ __forceinline__ void sts_u32(uint32_t a, uint32_t v) { asm volatile("st.shared.u32 [%0], %1;" :: "r"(a), "r"(v) : "memory"); }
__device__ __forceinline__ void stsm_x4(uint32_t a, uint32_t r0, uint32_t r1, uint32_t r2, uint32_t r3) {
  asm volatile("stmatrix.sync.aligned.m8n8.x4.shared.b16 [%0], {%1,%2,%3,%4};" :: "r"(a), "r"(r0), "r"(r1), "r"(r2), "r"(r3) : "memory");
}
__device__ __forceinline__ void stsm_x2(uint32_t a, uint32_t r0, uint32_t r1) {
  asm volatile("stmatrix.sync.aligned.m8n8.x2.shared.b16 [%0], {%1,%2};" :: "r"(a), "r"(r0), "r"(r1) : "memory");
}
__device__ __forceinline__ void stsm_x4_t(uint32_t a, uint32_t r0, uint32_t r1, uint32_t r2, uint32_t r3) {
  asm volatile("stmatrix.sync.aligned.m8n8.x4.trans.shared.b16 [%0], {%1,%2,%3,%4};" :: "r"(a), "r"(r0), "r"(r1), "r"(r2), "r"(r3) : "memory");
}
__device__ __forceinline__ void ldsm_x4(uint32_t a, uint32_t& r0, uint32_t& r1, uint32_t& r2, uint32_t& r3) {
  asm volatile("ldmatrix.sync.aligned.m8n8.x4.shared.b16 {%0,%1,%2,%3}, [%4];" : "=r"(r0), "=r"(r1), "=r"(r2), "=r"(r3) : "r"(a) : "memory");
}
__device__ __forceinline__ void ldsm_x2(uint32_t a, uint32_t& r0, uint32_t& r1) {
  asm volatile("ldmatrix.sync.aligned.m8n8.x2.shared.b16 {%0,%1}, [%2];" : "=r"(r0), "=r"(r1) : "r"(a) : "memory");
}
__device__ __forceinline__ uint32_t pack_bf16(float lo, float hi) { uint32_t r; asm("cvt.rn.bf16x2.f32 %0, %1, %2;" : "=r"(r) : "f"(hi), "f"(lo)); return r; }
__device__ __forceinline__ float bf_lo(uint32_t w) { return __uint_as_float(w << 16); }
__device__ __forceinline__ float bf_hi(uint32_t w) { return __uint_as_float(w & 0xFFFF0000u); }
__device__ __forceinline__ uint32_t hsub2(uint32_t a, uint32_t b) { uint32_t r; asm("sub.rn.bf16x2 %0, %1, %2;" : "=r"(r) : "r"(a), "r"(b)); return r; }
__device__ __forceinline__ uint32_t hadd2(uint32_t a, uint32_t b) { uint32_t r; asm("add.rn.bf16x2 %0, %1, %2;" : "=r"(r) : "r"(a), "r"(b)); return r; }
__device__ __forceinline__ uint32_t hmul2(uint32_t a, uint32_t b) { uint32_t r; asm("mul.rn.bf16x2 %0, %1, %2;" : "=r"(r) : "r"(a), "r"(b)); return r; }
__device__ __forceinline__ uint32_t hfma2(uint32_t a, uint32_t b, uint32_t c) { uint32_t r; asm("fma.rn.bf16x2 %0, %1, %2, %3;" : "=r"(r) : "r"(a), "r"(b), "r"(c)); return r; }
__device__ __forceinline__ uint32_t dup_lo(uint32_t a) { uint32_t r; asm("{\n.reg .b16 l, h;\nmov.b32 {l, h}, %1;\nmov.b32 %0, {l, l};\n}\n" : "=r"(r) : "r"(a)); return r; }
__device__ __forceinline__ uint32_t dup_hi(uint32_t a) { uint32_t r; asm("{\n.reg .b16 l, h;\nmov.b32 {l, h}, %1;\nmov.b32 %0, {h, h};\n}\n" : "=r"(r) : "r"(a)); return r; }
__device__ __forceinline__ float ex2f(float x) { float r; asm("ex2.approx.ftz.f32 %0, %1;" : "=f"(r) : "f"(x)); return r; }
__device__ __forceinline__ float rcpf(float x) { float r; asm("rcp.approx.ftz.f32 %0, %1;" : "=f"(r) : "f"(x)); return r; }
__device__ __forceinline__ float gelu_s(float a, float c1, float c2, float hr) {
  float t; asm("tanh.approx.f32 %0, %1;" : "=f"(t) : "f"(a * fmaf(a * c2, a, c1)));
  return a * fmaf(t, hr, hr);
}
constexpr uint32_t SB_LOW = 0x400;
__device__ __forceinline__ uint64_t mk_desc(uint32_t off, uint32_t lbo, uint32_t sbo) {
  return (uint64_t)((SB_LOW + off) >> 4) | ((uint64_t)(lbo >> 4) << 16) | ((uint64_t)(sbo >> 4) << 32) | ((uint64_t)1 << 62);
}
__device__ __forceinline__ uint64_t mk_desc_ns(uint32_t off, uint32_t n) {
  return (uint64_t)((SB_LOW + off) >> 4) | ((uint64_t)n << 16) | ((uint64_t)8 << 32);
}
__device__ __forceinline__ int fresh_lane() { int l; asm volatile("mov.u32 %0, %%laneid;" : "=r"(l)); return l; }
__device__ __forceinline__ int fresh_lane2() { int l; asm volatile("mov.u32 %0, %%lanemask_lt;" : "=r"(l)); return __popc(l); }
#define LANE_VARS2 const int lane = fresh_lane2(), q = lane & 3, rr = lane >> 2, lm = lane >> 3, lr = lane & 7; (void)q; (void)rr; (void)lm; (void)lr
#define LANE_VARS const int lane = fresh_lane(), q = lane & 3, rr = lane >> 2, lm = lane >> 3, lr = lane & 7; (void)q; (void)rr; (void)lm; (void)lr
__device__ __forceinline__ float quad_sum(float v) {
  v += __shfl_xor_sync(0xffffffffu, v, 1);
  v += __shfl_xor_sync(0xffffffffu, v, 2);
  return v;
}

__device__ __forceinline__ void ensure_block(uint4 (&t)[7], const uint4* up, uint32_t par) {
  asm volatile("{\n.reg .pred p;\n.reg .u32 n, m, a;\n.reg .b128 t;\n.reg .b64 u;\nmov.u32 n, 0;\nWL:\nor.b32 m, %0, %4;\nand.b32 a, %0, %4;\nor.b32 m, m, %8;\nand.b32 a, a, %8;\nor.b32 m, m, %12;\nand.b32 a, a, %12;\nor.b32 m, m, %16;\nand.b32 a, a, %16;\nor.b32 m, m, %20;\nand.b32 a, a, %20;\nor.b32 m, m, %24;\nand.b32 a, a, %24;\nxor.b32 m, m, %30;\nxor.b32 a, a, %30;\nor.b32 m, m, a;\nand.b32 m, m, 1;\nsetp.ne.u32 p, m, 0;\nvote.sync.any.pred p, p, 0xffffffff;\n@!p bra WD;\nnanosleep.u32 100;\nld.relaxed.gpu.global.b128 t, [%28+0];\nmov.b128 {%0,%1,%2,%3}, t;\nld.relaxed.gpu.global.b128 t, [%28+512];\nmov.b128 {%4,%5,%6,%7}, t;\nld.relaxed.gpu.global.b128 t, [%28+1024];\nmov.b128 {%8,%9,%10,%11}, t;\nld.relaxed.gpu.global.b128 t, [%28+1536];\nmov.b128 {%12,%13,%14,%15}, t;\nld.relaxed.gpu.global.b128 t, [%28+2048];\nmov.b128 {%16,%17,%18,%19}, t;\nld.relaxed.gpu.global.b128 t, [%28+2560];\nmov.b128 {%20,%21,%22,%23}, t;\nld.relaxed.gpu.global.b128 t, [%28+3072];\nmov.b128 {%24,%25,%26,%27}, t;\nadd.u32 n, n, 1;\nsetp.lt.u32 p, n, %29;\n@p bra WL;\ntrap;\nWD:\nand.b32 %0, %0, 0xFFFFFFFE;\nand.b32 %4, %4, 0xFFFFFFFE;\nand.b32 %8, %8, 0xFFFFFFFE;\nand.b32 %12, %12, 0xFFFFFFFE;\nand.b32 %16, %16, 0xFFFFFFFE;\nand.b32 %20, %20, 0xFFFFFFFE;\nand.b32 %24, %24, 0xFFFFFFFE;\n}\n"
    : "+r"(t[0].x), "+r"(t[0].y), "+r"(t[0].z), "+r"(t[0].w), "+r"(t[1].x), "+r"(t[1].y), "+r"(t[1].z), "+r"(t[1].w), "+r"(t[2].x), "+r"(t[2].y), "+r"(t[2].z), "+r"(t[2].w), "+r"(t[3].x), "+r"(t[3].y), "+r"(t[3].z), "+r"(t[3].w), "+r"(t[4].x), "+r"(t[4].y), "+r"(t[4].z), "+r"(t[4].w), "+r"(t[5].x), "+r"(t[5].y), "+r"(t[5].z), "+r"(t[5].w), "+r"(t[6].x), "+r"(t[6].y), "+r"(t[6].z), "+r"(t[6].w)
    : "l"(up), "n"(SPIN_LIMIT), "r"(par) : "memory");
}
__device__ __forceinline__ void ensure_o(uint32_t (&of)[14][4], const void* p16, const void* p8, uint32_t par) {
  asm volatile("{\n.reg .pred p;\n.reg .u32 n, m, a;\n.reg .b128 t;\n.reg .b64 u;\nmov.u32 n, 0;\nWL:\nor.b32 m, %0, %4;\nand.b32 a, %0, %4;\nor.b32 m, m, %8;\nand.b32 a, a, %8;\nor.b32 m, m, %12;\nand.b32 a, a, %12;\nor.b32 m, m, %16;\nand.b32 a, a, %16;\nor.b32 m, m, %20;\nand.b32 a, a, %20;\nor.b32 m, m, %24;\nand.b32 a, a, %24;\nor.b32 m, m, %28;\nand.b32 a, a, %28;\nor.b32 m, m, %32;\nand.b32 a, a, %32;\nor.b32 m, m, %36;\nand.b32 a, a, %36;\nor.b32 m, m, %40;\nand.b32 a, a, %40;\nor.b32 m, m, %44;\nand.b32 a, a, %44;\nor.b32 m, m, %48;\nand.b32 a, a, %48;\nor.b32 m, m, %50;\nand.b32 a, a, %50;\nor.b32 m, m, %52;\nand.b32 a, a, %52;\nor.b32 m, m, %54;\nand.b32 a, a, %54;\nxor.b32 m, m, %59;\nxor.b32 a, a, %59;\nor.b32 m, m, a;\nand.b32 m, m, 1;\nsetp.ne.u32 p, m, 0;\nvote.sync.any.pred p, p, 0xffffffff;\n@!p bra WD;\nnanosleep.u32 100;\nld.relaxed.gpu.global.b128 t, [%56+0];\nmov.b128 {%0,%1,%2,%3}, t;\nld.relaxed.gpu.global.b128 t, [%56+512];\nmov.b128 {%4,%5,%6,%7}, t;\nld.relaxed.gpu.global.b128 t, [%56+1024];\nmov.b128 {%8,%9,%10,%11}, t;\nld.relaxed.gpu.global.b128 t, [%56+14336];\nmov.b128 {%12,%13,%14,%15}, t;\nld.relaxed.gpu.global.b128 t, [%56+14848];\nmov.b128 {%16,%17,%18,%19}, t;\nld.relaxed.gpu.global.b128 t, [%56+15360];\nmov.b128 {%20,%21,%22,%23}, t;\nld.relaxed.gpu.global.b128 t, [%56+28672];\nmov.b128 {%24,%25,%26,%27}, t;\nld.relaxed.gpu.global.b128 t, [%56+29184];\nmov.b128 {%28,%29,%30,%31}, t;\nld.relaxed.gpu.global.b128 t, [%56+29696];\nmov.b128 {%32,%33,%34,%35}, t;\nld.relaxed.gpu.global.b128 t, [%56+43008];\nmov.b128 {%36,%37,%38,%39}, t;\nld.relaxed.gpu.global.b128 t, [%56+43520];\nmov.b128 {%40,%41,%42,%43}, t;\nld.relaxed.gpu.global.b128 t, [%56+44032];\nmov.b128 {%44,%45,%46,%47}, t;\nld.relaxed.gpu.global.b64 u, [%57+0];\nmov.b64 {%48,%49}, u;\nld.relaxed.gpu.global.b64 u, [%57+14336];\nmov.b64 {%50,%51}, u;\nld.relaxed.gpu.global.b64 u, [%57+28672];\nmov.b64 {%52,%53}, u;\nld.relaxed.gpu.global.b64 u, [%57+43008];\nmov.b64 {%54,%55}, u;\nadd.u32 n, n, 1;\nsetp.lt.u32 p, n, %58;\n@p bra WL;\ntrap;\nWD:\nand.b32 %0, %0, 0xFFFFFFFE;\nand.b32 %4, %4, 0xFFFFFFFE;\nand.b32 %8, %8, 0xFFFFFFFE;\nand.b32 %12, %12, 0xFFFFFFFE;\nand.b32 %16, %16, 0xFFFFFFFE;\nand.b32 %20, %20, 0xFFFFFFFE;\nand.b32 %24, %24, 0xFFFFFFFE;\nand.b32 %28, %28, 0xFFFFFFFE;\nand.b32 %32, %32, 0xFFFFFFFE;\nand.b32 %36, %36, 0xFFFFFFFE;\nand.b32 %40, %40, 0xFFFFFFFE;\nand.b32 %44, %44, 0xFFFFFFFE;\nand.b32 %48, %48, 0xFFFFFFFE;\nand.b32 %50, %50, 0xFFFFFFFE;\nand.b32 %52, %52, 0xFFFFFFFE;\nand.b32 %54, %54, 0xFFFFFFFE;\n}\n"
    : "+r"(of[0][0]), "+r"(of[0][1]), "+r"(of[0][2]), "+r"(of[0][3]), "+r"(of[1][0]), "+r"(of[1][1]), "+r"(of[1][2]), "+r"(of[1][3]), "+r"(of[2][0]), "+r"(of[2][1]), "+r"(of[2][2]), "+r"(of[2][3]), "+r"(of[3][0]), "+r"(of[3][1]), "+r"(of[3][2]), "+r"(of[3][3]), "+r"(of[4][0]), "+r"(of[4][1]), "+r"(of[4][2]), "+r"(of[4][3]), "+r"(of[5][0]), "+r"(of[5][1]), "+r"(of[5][2]), "+r"(of[5][3]), "+r"(of[6][0]), "+r"(of[6][1]), "+r"(of[6][2]), "+r"(of[6][3]), "+r"(of[7][0]), "+r"(of[7][1]), "+r"(of[7][2]), "+r"(of[7][3]), "+r"(of[8][0]), "+r"(of[8][1]), "+r"(of[8][2]), "+r"(of[8][3]), "+r"(of[9][0]), "+r"(of[9][1]), "+r"(of[9][2]), "+r"(of[9][3]), "+r"(of[10][0]), "+r"(of[10][1]), "+r"(of[10][2]), "+r"(of[10][3]), "+r"(of[11][0]), "+r"(of[11][1]), "+r"(of[11][2]), "+r"(of[11][3]), "+r"(of[12][0]), "+r"(of[12][1]), "+r"(of[12][2]), "+r"(of[12][3]), "+r"(of[13][0]), "+r"(of[13][1]), "+r"(of[13][2]), "+r"(of[13][3])
    : "l"(p16), "l"(p8), "n"(SPIN_LIMIT), "r"(par) : "memory");
}

template<int TA, int TB>
__device__ __forceinline__ void wgmma_ss_n112(float* d, uint64_t da, uint64_t db, int sc) {
  asm volatile("{\n.reg .pred p;\nsetp.ne.b32 p, %58, 0;\n"
    "wgmma.mma_async.sync.aligned.m64n112k16.f32.bf16.bf16 {%0, %1, %2, %3, %4, %5, %6, %7, %8, %9, %10, %11, %12, %13, %14, %15, %16, %17, %18, %19, %20, %21, %22, %23, %24, %25, %26, %27, %28, %29, %30, %31, %32, %33, %34, %35, %36, %37, %38, %39, %40, %41, %42, %43, %44, %45, %46, %47, %48, %49, %50, %51, %52, %53, %54, %55}, %56, %57, p, 1, 1, %59, %60;\n}\n"
    : "+f"(d[0]), "+f"(d[1]), "+f"(d[2]), "+f"(d[3]), "+f"(d[4]), "+f"(d[5]), "+f"(d[6]), "+f"(d[7]), "+f"(d[8]), "+f"(d[9]), "+f"(d[10]), "+f"(d[11]), "+f"(d[12]), "+f"(d[13]), "+f"(d[14]), "+f"(d[15]), "+f"(d[16]), "+f"(d[17]), "+f"(d[18]), "+f"(d[19]), "+f"(d[20]), "+f"(d[21]), "+f"(d[22]), "+f"(d[23]), "+f"(d[24]), "+f"(d[25]), "+f"(d[26]), "+f"(d[27]), "+f"(d[28]), "+f"(d[29]), "+f"(d[30]), "+f"(d[31]), "+f"(d[32]), "+f"(d[33]), "+f"(d[34]), "+f"(d[35]), "+f"(d[36]), "+f"(d[37]), "+f"(d[38]), "+f"(d[39]), "+f"(d[40]), "+f"(d[41]), "+f"(d[42]), "+f"(d[43]), "+f"(d[44]), "+f"(d[45]), "+f"(d[46]), "+f"(d[47]), "+f"(d[48]), "+f"(d[49]), "+f"(d[50]), "+f"(d[51]), "+f"(d[52]), "+f"(d[53]), "+f"(d[54]), "+f"(d[55])
    : "l"(da), "l"(db), "r"(sc), "n"(TA), "n"(TB));
}

template<int TA, int TB>
__device__ __forceinline__ void wgmma_ss_n224(float* d, uint64_t da, uint64_t db, int sc) {
  asm volatile("{\n.reg .pred p;\nsetp.ne.b32 p, %114, 0;\n"
    "wgmma.mma_async.sync.aligned.m64n224k16.f32.bf16.bf16 {%0, %1, %2, %3, %4, %5, %6, %7, %8, %9, %10, %11, %12, %13, %14, %15, %16, %17, %18, %19, %20, %21, %22, %23, %24, %25, %26, %27, %28, %29, %30, %31, %32, %33, %34, %35, %36, %37, %38, %39, %40, %41, %42, %43, %44, %45, %46, %47, %48, %49, %50, %51, %52, %53, %54, %55, %56, %57, %58, %59, %60, %61, %62, %63, %64, %65, %66, %67, %68, %69, %70, %71, %72, %73, %74, %75, %76, %77, %78, %79, %80, %81, %82, %83, %84, %85, %86, %87, %88, %89, %90, %91, %92, %93, %94, %95, %96, %97, %98, %99, %100, %101, %102, %103, %104, %105, %106, %107, %108, %109, %110, %111}, %112, %113, p, 1, 1, %115, %116;\n}\n"
    : "+f"(d[0]), "+f"(d[1]), "+f"(d[2]), "+f"(d[3]), "+f"(d[4]), "+f"(d[5]), "+f"(d[6]), "+f"(d[7]), "+f"(d[8]), "+f"(d[9]), "+f"(d[10]), "+f"(d[11]), "+f"(d[12]), "+f"(d[13]), "+f"(d[14]), "+f"(d[15]), "+f"(d[16]), "+f"(d[17]), "+f"(d[18]), "+f"(d[19]), "+f"(d[20]), "+f"(d[21]), "+f"(d[22]), "+f"(d[23]), "+f"(d[24]), "+f"(d[25]), "+f"(d[26]), "+f"(d[27]), "+f"(d[28]), "+f"(d[29]), "+f"(d[30]), "+f"(d[31]), "+f"(d[32]), "+f"(d[33]), "+f"(d[34]), "+f"(d[35]), "+f"(d[36]), "+f"(d[37]), "+f"(d[38]), "+f"(d[39]), "+f"(d[40]), "+f"(d[41]), "+f"(d[42]), "+f"(d[43]), "+f"(d[44]), "+f"(d[45]), "+f"(d[46]), "+f"(d[47]), "+f"(d[48]), "+f"(d[49]), "+f"(d[50]), "+f"(d[51]), "+f"(d[52]), "+f"(d[53]), "+f"(d[54]), "+f"(d[55]), "+f"(d[56]), "+f"(d[57]), "+f"(d[58]), "+f"(d[59]), "+f"(d[60]), "+f"(d[61]), "+f"(d[62]), "+f"(d[63]), "+f"(d[64]), "+f"(d[65]), "+f"(d[66]), "+f"(d[67]), "+f"(d[68]), "+f"(d[69]), "+f"(d[70]), "+f"(d[71]), "+f"(d[72]), "+f"(d[73]), "+f"(d[74]), "+f"(d[75]), "+f"(d[76]), "+f"(d[77]), "+f"(d[78]), "+f"(d[79]), "+f"(d[80]), "+f"(d[81]), "+f"(d[82]), "+f"(d[83]), "+f"(d[84]), "+f"(d[85]), "+f"(d[86]), "+f"(d[87]), "+f"(d[88]), "+f"(d[89]), "+f"(d[90]), "+f"(d[91]), "+f"(d[92]), "+f"(d[93]), "+f"(d[94]), "+f"(d[95]), "+f"(d[96]), "+f"(d[97]), "+f"(d[98]), "+f"(d[99]), "+f"(d[100]), "+f"(d[101]), "+f"(d[102]), "+f"(d[103]), "+f"(d[104]), "+f"(d[105]), "+f"(d[106]), "+f"(d[107]), "+f"(d[108]), "+f"(d[109]), "+f"(d[110]), "+f"(d[111])
    : "l"(da), "l"(db), "r"(sc), "n"(TA), "n"(TB));
}
__device__ __forceinline__ void wgmma_rt_n112(float* d, uint32_t a0, uint32_t a1, uint32_t a2, uint32_t a3, uint64_t db, bool accumulate) {
  if (accumulate) {
    asm volatile("{\n.reg .pred p;\nsetp.ne.b32 p, 1, 0;\n"
      "wgmma.mma_async.sync.aligned.m64n112k16.f32.bf16.bf16 {%0, %1, %2, %3, %4, %5, %6, %7, %8, %9, %10, %11, %12, %13, %14, %15, %16, %17, %18, %19, %20, %21, %22, %23, %24, %25, %26, %27, %28, %29, %30, %31, %32, %33, %34, %35, %36, %37, %38, %39, %40, %41, %42, %43, %44, %45, %46, %47, %48, %49, %50, %51, %52, %53, %54, %55}, {%56, %57, %58, %59}, %60, p, 1, 1, 1;\n}\n"
      : "+f"(d[0]), "+f"(d[1]), "+f"(d[2]), "+f"(d[3]), "+f"(d[4]), "+f"(d[5]), "+f"(d[6]), "+f"(d[7]), "+f"(d[8]), "+f"(d[9]), "+f"(d[10]), "+f"(d[11]), "+f"(d[12]), "+f"(d[13]), "+f"(d[14]), "+f"(d[15]), "+f"(d[16]), "+f"(d[17]), "+f"(d[18]), "+f"(d[19]), "+f"(d[20]), "+f"(d[21]), "+f"(d[22]), "+f"(d[23]), "+f"(d[24]), "+f"(d[25]), "+f"(d[26]), "+f"(d[27]), "+f"(d[28]), "+f"(d[29]), "+f"(d[30]), "+f"(d[31]), "+f"(d[32]), "+f"(d[33]), "+f"(d[34]), "+f"(d[35]), "+f"(d[36]), "+f"(d[37]), "+f"(d[38]), "+f"(d[39]), "+f"(d[40]), "+f"(d[41]), "+f"(d[42]), "+f"(d[43]), "+f"(d[44]), "+f"(d[45]), "+f"(d[46]), "+f"(d[47]), "+f"(d[48]), "+f"(d[49]), "+f"(d[50]), "+f"(d[51]), "+f"(d[52]), "+f"(d[53]), "+f"(d[54]), "+f"(d[55])
      : "r"(a0), "r"(a1), "r"(a2), "r"(a3), "l"(db));
  } else {
    asm volatile("{\n.reg .pred p;\nsetp.ne.b32 p, 0, 0;\n"
      "wgmma.mma_async.sync.aligned.m64n112k16.f32.bf16.bf16 {%0, %1, %2, %3, %4, %5, %6, %7, %8, %9, %10, %11, %12, %13, %14, %15, %16, %17, %18, %19, %20, %21, %22, %23, %24, %25, %26, %27, %28, %29, %30, %31, %32, %33, %34, %35, %36, %37, %38, %39, %40, %41, %42, %43, %44, %45, %46, %47, %48, %49, %50, %51, %52, %53, %54, %55}, {%56, %57, %58, %59}, %60, p, 1, 1, 1;\n}\n"
      : "=f"(d[0]), "=f"(d[1]), "=f"(d[2]), "=f"(d[3]), "=f"(d[4]), "=f"(d[5]), "=f"(d[6]), "=f"(d[7]), "=f"(d[8]), "=f"(d[9]), "=f"(d[10]), "=f"(d[11]), "=f"(d[12]), "=f"(d[13]), "=f"(d[14]), "=f"(d[15]), "=f"(d[16]), "=f"(d[17]), "=f"(d[18]), "=f"(d[19]), "=f"(d[20]), "=f"(d[21]), "=f"(d[22]), "=f"(d[23]), "=f"(d[24]), "=f"(d[25]), "=f"(d[26]), "=f"(d[27]), "=f"(d[28]), "=f"(d[29]), "=f"(d[30]), "=f"(d[31]), "=f"(d[32]), "=f"(d[33]), "=f"(d[34]), "=f"(d[35]), "=f"(d[36]), "=f"(d[37]), "=f"(d[38]), "=f"(d[39]), "=f"(d[40]), "=f"(d[41]), "=f"(d[42]), "=f"(d[43]), "=f"(d[44]), "=f"(d[45]), "=f"(d[46]), "=f"(d[47]), "=f"(d[48]), "=f"(d[49]), "=f"(d[50]), "=f"(d[51]), "=f"(d[52]), "=f"(d[53]), "=f"(d[54]), "=f"(d[55])
      : "r"(a0), "r"(a1), "r"(a2), "r"(a3), "l"(db));
  }
}

__device__ __forceinline__ void wgmma_rt_n128(float* d, uint32_t a0, uint32_t a1, uint32_t a2, uint32_t a3, uint64_t db, bool accumulate) {
  if (accumulate) {
    asm volatile("{\n.reg .pred p;\nsetp.ne.b32 p, 1, 0;\n"
      "wgmma.mma_async.sync.aligned.m64n128k16.f32.bf16.bf16 {%0, %1, %2, %3, %4, %5, %6, %7, %8, %9, %10, %11, %12, %13, %14, %15, %16, %17, %18, %19, %20, %21, %22, %23, %24, %25, %26, %27, %28, %29, %30, %31, %32, %33, %34, %35, %36, %37, %38, %39, %40, %41, %42, %43, %44, %45, %46, %47, %48, %49, %50, %51, %52, %53, %54, %55, %56, %57, %58, %59, %60, %61, %62, %63}, {%64, %65, %66, %67}, %68, p, 1, 1, 1;\n}\n"
      : "+f"(d[0]), "+f"(d[1]), "+f"(d[2]), "+f"(d[3]), "+f"(d[4]), "+f"(d[5]), "+f"(d[6]), "+f"(d[7]), "+f"(d[8]), "+f"(d[9]), "+f"(d[10]), "+f"(d[11]), "+f"(d[12]), "+f"(d[13]), "+f"(d[14]), "+f"(d[15]), "+f"(d[16]), "+f"(d[17]), "+f"(d[18]), "+f"(d[19]), "+f"(d[20]), "+f"(d[21]), "+f"(d[22]), "+f"(d[23]), "+f"(d[24]), "+f"(d[25]), "+f"(d[26]), "+f"(d[27]), "+f"(d[28]), "+f"(d[29]), "+f"(d[30]), "+f"(d[31]), "+f"(d[32]), "+f"(d[33]), "+f"(d[34]), "+f"(d[35]), "+f"(d[36]), "+f"(d[37]), "+f"(d[38]), "+f"(d[39]), "+f"(d[40]), "+f"(d[41]), "+f"(d[42]), "+f"(d[43]), "+f"(d[44]), "+f"(d[45]), "+f"(d[46]), "+f"(d[47]), "+f"(d[48]), "+f"(d[49]), "+f"(d[50]), "+f"(d[51]), "+f"(d[52]), "+f"(d[53]), "+f"(d[54]), "+f"(d[55]), "+f"(d[56]), "+f"(d[57]), "+f"(d[58]), "+f"(d[59]), "+f"(d[60]), "+f"(d[61]), "+f"(d[62]), "+f"(d[63])
      : "r"(a0), "r"(a1), "r"(a2), "r"(a3), "l"(db));
  } else {
    asm volatile("{\n.reg .pred p;\nsetp.ne.b32 p, 0, 0;\n"
      "wgmma.mma_async.sync.aligned.m64n128k16.f32.bf16.bf16 {%0, %1, %2, %3, %4, %5, %6, %7, %8, %9, %10, %11, %12, %13, %14, %15, %16, %17, %18, %19, %20, %21, %22, %23, %24, %25, %26, %27, %28, %29, %30, %31, %32, %33, %34, %35, %36, %37, %38, %39, %40, %41, %42, %43, %44, %45, %46, %47, %48, %49, %50, %51, %52, %53, %54, %55, %56, %57, %58, %59, %60, %61, %62, %63}, {%64, %65, %66, %67}, %68, p, 1, 1, 1;\n}\n"
      : "=f"(d[0]), "=f"(d[1]), "=f"(d[2]), "=f"(d[3]), "=f"(d[4]), "=f"(d[5]), "=f"(d[6]), "=f"(d[7]), "=f"(d[8]), "=f"(d[9]), "=f"(d[10]), "=f"(d[11]), "=f"(d[12]), "=f"(d[13]), "=f"(d[14]), "=f"(d[15]), "=f"(d[16]), "=f"(d[17]), "=f"(d[18]), "=f"(d[19]), "=f"(d[20]), "=f"(d[21]), "=f"(d[22]), "=f"(d[23]), "=f"(d[24]), "=f"(d[25]), "=f"(d[26]), "=f"(d[27]), "=f"(d[28]), "=f"(d[29]), "=f"(d[30]), "=f"(d[31]), "=f"(d[32]), "=f"(d[33]), "=f"(d[34]), "=f"(d[35]), "=f"(d[36]), "=f"(d[37]), "=f"(d[38]), "=f"(d[39]), "=f"(d[40]), "=f"(d[41]), "=f"(d[42]), "=f"(d[43]), "=f"(d[44]), "=f"(d[45]), "=f"(d[46]), "=f"(d[47]), "=f"(d[48]), "=f"(d[49]), "=f"(d[50]), "=f"(d[51]), "=f"(d[52]), "=f"(d[53]), "=f"(d[54]), "=f"(d[55]), "=f"(d[56]), "=f"(d[57]), "=f"(d[58]), "=f"(d[59]), "=f"(d[60]), "=f"(d[61]), "=f"(d[62]), "=f"(d[63])
      : "r"(a0), "r"(a1), "r"(a2), "r"(a3), "l"(db));
  }
}

__device__ __forceinline__ void wgmma_rt_n168(float* d, uint32_t a0, uint32_t a1, uint32_t a2, uint32_t a3, uint64_t db, bool accumulate) {
  if (accumulate) {
    asm volatile("{\n.reg .pred p;\nsetp.ne.b32 p, 1, 0;\n"
      "wgmma.mma_async.sync.aligned.m64n168k16.f32.bf16.bf16 {%0, %1, %2, %3, %4, %5, %6, %7, %8, %9, %10, %11, %12, %13, %14, %15, %16, %17, %18, %19, %20, %21, %22, %23, %24, %25, %26, %27, %28, %29, %30, %31, %32, %33, %34, %35, %36, %37, %38, %39, %40, %41, %42, %43, %44, %45, %46, %47, %48, %49, %50, %51, %52, %53, %54, %55, %56, %57, %58, %59, %60, %61, %62, %63, %64, %65, %66, %67, %68, %69, %70, %71, %72, %73, %74, %75, %76, %77, %78, %79, %80, %81, %82, %83}, {%84, %85, %86, %87}, %88, p, 1, 1, 1;\n}\n"
      : "+f"(d[0]), "+f"(d[1]), "+f"(d[2]), "+f"(d[3]), "+f"(d[4]), "+f"(d[5]), "+f"(d[6]), "+f"(d[7]), "+f"(d[8]), "+f"(d[9]), "+f"(d[10]), "+f"(d[11]), "+f"(d[12]), "+f"(d[13]), "+f"(d[14]), "+f"(d[15]), "+f"(d[16]), "+f"(d[17]), "+f"(d[18]), "+f"(d[19]), "+f"(d[20]), "+f"(d[21]), "+f"(d[22]), "+f"(d[23]), "+f"(d[24]), "+f"(d[25]), "+f"(d[26]), "+f"(d[27]), "+f"(d[28]), "+f"(d[29]), "+f"(d[30]), "+f"(d[31]), "+f"(d[32]), "+f"(d[33]), "+f"(d[34]), "+f"(d[35]), "+f"(d[36]), "+f"(d[37]), "+f"(d[38]), "+f"(d[39]), "+f"(d[40]), "+f"(d[41]), "+f"(d[42]), "+f"(d[43]), "+f"(d[44]), "+f"(d[45]), "+f"(d[46]), "+f"(d[47]), "+f"(d[48]), "+f"(d[49]), "+f"(d[50]), "+f"(d[51]), "+f"(d[52]), "+f"(d[53]), "+f"(d[54]), "+f"(d[55]), "+f"(d[56]), "+f"(d[57]), "+f"(d[58]), "+f"(d[59]), "+f"(d[60]), "+f"(d[61]), "+f"(d[62]), "+f"(d[63]), "+f"(d[64]), "+f"(d[65]), "+f"(d[66]), "+f"(d[67]), "+f"(d[68]), "+f"(d[69]), "+f"(d[70]), "+f"(d[71]), "+f"(d[72]), "+f"(d[73]), "+f"(d[74]), "+f"(d[75]), "+f"(d[76]), "+f"(d[77]), "+f"(d[78]), "+f"(d[79]), "+f"(d[80]), "+f"(d[81]), "+f"(d[82]), "+f"(d[83])
      : "r"(a0), "r"(a1), "r"(a2), "r"(a3), "l"(db));
  } else {
    asm volatile("{\n.reg .pred p;\nsetp.ne.b32 p, 0, 0;\n"
      "wgmma.mma_async.sync.aligned.m64n168k16.f32.bf16.bf16 {%0, %1, %2, %3, %4, %5, %6, %7, %8, %9, %10, %11, %12, %13, %14, %15, %16, %17, %18, %19, %20, %21, %22, %23, %24, %25, %26, %27, %28, %29, %30, %31, %32, %33, %34, %35, %36, %37, %38, %39, %40, %41, %42, %43, %44, %45, %46, %47, %48, %49, %50, %51, %52, %53, %54, %55, %56, %57, %58, %59, %60, %61, %62, %63, %64, %65, %66, %67, %68, %69, %70, %71, %72, %73, %74, %75, %76, %77, %78, %79, %80, %81, %82, %83}, {%84, %85, %86, %87}, %88, p, 1, 1, 1;\n}\n"
      : "=f"(d[0]), "=f"(d[1]), "=f"(d[2]), "=f"(d[3]), "=f"(d[4]), "=f"(d[5]), "=f"(d[6]), "=f"(d[7]), "=f"(d[8]), "=f"(d[9]), "=f"(d[10]), "=f"(d[11]), "=f"(d[12]), "=f"(d[13]), "=f"(d[14]), "=f"(d[15]), "=f"(d[16]), "=f"(d[17]), "=f"(d[18]), "=f"(d[19]), "=f"(d[20]), "=f"(d[21]), "=f"(d[22]), "=f"(d[23]), "=f"(d[24]), "=f"(d[25]), "=f"(d[26]), "=f"(d[27]), "=f"(d[28]), "=f"(d[29]), "=f"(d[30]), "=f"(d[31]), "=f"(d[32]), "=f"(d[33]), "=f"(d[34]), "=f"(d[35]), "=f"(d[36]), "=f"(d[37]), "=f"(d[38]), "=f"(d[39]), "=f"(d[40]), "=f"(d[41]), "=f"(d[42]), "=f"(d[43]), "=f"(d[44]), "=f"(d[45]), "=f"(d[46]), "=f"(d[47]), "=f"(d[48]), "=f"(d[49]), "=f"(d[50]), "=f"(d[51]), "=f"(d[52]), "=f"(d[53]), "=f"(d[54]), "=f"(d[55]), "=f"(d[56]), "=f"(d[57]), "=f"(d[58]), "=f"(d[59]), "=f"(d[60]), "=f"(d[61]), "=f"(d[62]), "=f"(d[63]), "=f"(d[64]), "=f"(d[65]), "=f"(d[66]), "=f"(d[67]), "=f"(d[68]), "=f"(d[69]), "=f"(d[70]), "=f"(d[71]), "=f"(d[72]), "=f"(d[73]), "=f"(d[74]), "=f"(d[75]), "=f"(d[76]), "=f"(d[77]), "=f"(d[78]), "=f"(d[79]), "=f"(d[80]), "=f"(d[81]), "=f"(d[82]), "=f"(d[83])
      : "r"(a0), "r"(a1), "r"(a2), "r"(a3), "l"(db));
  }
}

__host__ __device__ constexpr uint32_t p2_off(int kc) { return kc < 4 ? 14 * BOX1 + (uint32_t)kc * P2ST : (uint32_t)(kc - 4) * P2ST; }
__host__ __device__ constexpr uint32_t p3_off(int kc) { return (uint32_t)((1 + kc / 2) & 3) * STAGE2 + (uint32_t)(kc & 1) * P3ST; }
__host__ __device__ constexpr uint32_t ub_off(int b) { return b == 0 ? Q_OFF : 3 * STAGE2 + W3BLK - (b == 1 ? 28672u : 0u); }
__host__ __device__ constexpr uint32_t ub_str(int b) { return b < 2 ? 14336u : 0u - (3 * STAGE2 + W3BLK); }
__host__ __device__ constexpr uint32_t sa_off(int e) { return e == 0 ? 3 * STAGE2 : (e == 1 ? 0u : STAGE2 + (uint32_t)(e - 2) * 16384); }
__host__ __device__ constexpr uint32_t sz_off(int e) { return (e < 2 ? 3 * STAGE2 : 0u) + 16384 + (uint32_t)(e & 1) * ZBLK; }
__host__ __device__ constexpr uint32_t w3_off(int b) { return b == 0 ? 3 * STAGE2 : (b < 4 ? (uint32_t)(b - 1) * W3BLK : OB_OFF + (uint32_t)(b - 4) * W3BLK); }

struct Params {
  const __nv_bfloat16* x;
  const __nv_bfloat16* wqkv;
  const __nv_bfloat16* win;
  const __nv_bfloat16* wsp;
  const __nv_bfloat16* bsp;
  const __nv_bfloat16* wo;
  const __nv_bfloat16* wout;
  __nv_bfloat16* out;
  Scratch* S;
  uint32_t zero;
};

struct HeadRow { uint4 a, b, c; uint2 d; };
__device__ __forceinline__ HeadRow ld_head(uint32_t a16, uint32_t a8) {
  HeadRow r; r.a = lds_v4(a16); r.b = lds_v4(a16 + 16); r.c = lds_v4(a16 + 32); r.d = lds_v2(a8); return r;
}
__device__ __forceinline__ void attn_scores(uint32_t sb, int g, int lane, int i) {
  const int tl = 16 * g + (lane & 7) + ((lane >> 4) << 3), h = (lane >> 3) & 1;
  const uint32_t o16 = sb + (uint32_t)tl * 112 + h * 64, o8 = sb + (uint32_t)tl * 112 + 48 + h * 8;
  const HeadRow qv = ld_head(o16 + Q_OFF, o8 + Q_OFF);
  const int tok = 128 * i + tl;
  float l[8];
  const float sc = 0.18898223650461362f * 1.4426950408889634f * __uint_as_float(lds_u32(sb + RS_OFF + (uint32_t)tl * 4));
  float mx = -INFINITY;
  #pragma unroll
  for (int w = 0; w < 8; w++) l[w] = 0.f;
  #pragma unroll 1
  for (int wp = 0; wp < 8; wp += 2) {
    #pragma unroll
    for (int w = 0; w < 6; w++) l[w] = l[w + 2];
    #pragma unroll
    for (int e = 0; e < 2; e++) {
      const uint32_t ko = K_OFF + 16 * 112 - 224 * (wp + e);
      const HeadRow t = ld_head(o16 + ko, o8 + ko);
      uint32_t s0 = hmul2(qv.a.x, t.a.x), s1 = hmul2(qv.a.y, t.a.y), s2 = hmul2(qv.a.z, t.a.z), s3 = hmul2(qv.a.w, t.a.w);
      s0 = hfma2(qv.b.x, t.b.x, s0); s1 = hfma2(qv.b.y, t.b.y, s1); s2 = hfma2(qv.b.z, t.b.z, s2); s3 = hfma2(qv.b.w, t.b.w, s3);
      s0 = hfma2(qv.c.x, t.c.x, s0); s1 = hfma2(qv.c.y, t.c.y, s1); s2 = hfma2(qv.c.z, t.c.z, s2); s3 = hfma2(qv.c.w, t.c.w, s3);
      s0 = hfma2(qv.d.x, t.d.x, s0); s1 = hfma2(qv.d.y, t.d.y, s1);
      const float d = ((bf_lo(s0) + bf_hi(s0)) + (bf_lo(s1) + bf_hi(s1))) + ((bf_lo(s2) + bf_hi(s2)) + (bf_lo(s3) + bf_hi(s3)));
      l[6 + e] = (tok - 2 * (wp + e) >= 0) ? d * sc : -INFINITY;
      mx = fmaxf(mx, l[6 + e]);
    }
  }
  float sum = 0.f;
  #pragma unroll
  for (int w = 0; w < 8; w++) { l[w] = ex2f(l[w] - mx); sum += l[w]; }
  const float inv = rcpf(sum);
  __syncwarp();
  sts_v4(sb + Q_OFF + (uint32_t)tl * 112 + h * 16,
         make_uint4(pack_bf16(l[0] * inv, l[1] * inv), pack_bf16(l[2] * inv, l[3] * inv), pack_bf16(l[4] * inv, l[5] * inv), pack_bf16(l[6] * inv, l[7] * inv)));
}

__device__ __forceinline__ void attn_pv(uint32_t sb, int seg, int par, int lane, uint32_t mark) {
  const int wc = lane < 28 ? lane : 27;
  const int t0 = 32 * seg + par;
  const uint32_t va = sb + V_OFF + (uint32_t)(t0 + 16) * 112 + wc * 4;
  const uint32_t pa = sb + Q_OFF + (uint32_t)t0 * 112 + (wc >= 14 ? 16 : 0);
  const int nt = wc >> 2;
  const uint32_t es = nt < 6 ? 16 : 8;
  const uint32_t oa = sb + K_OFF + (uint32_t)(2 * seg) * 1792 + (nt >> 1) * 512 + (nt & 1) * 8 + (uint32_t)(par * 4 + (wc & 3)) * es;
  const uint32_t mk1 = (nt & 1) ? 0xFFFFFFFFu : 0xFFFFFFFEu, mk2 = (nt & 1) ? 0u : mark;
  uint32_t vw[15];
  #pragma unroll
  for (int n = 0; n < 7; n++) vw[8 + n] = lds_u32(va + 224 * (n - 7));
  #pragma unroll 1
  for (int hb = 0; hb < 2; hb++) {
    uint32_t o[8];
    #pragma unroll
    for (int n = 0; n < 7; n++) vw[n] = vw[8 + n];
    #pragma unroll
    for (int n = 0; n < 8; n++) {
      vw[7 + n] = lds_u32(va + hb * 1792 + 224 * n);
      const uint4 pw = lds_v4(pa + hb * 1792 + n * 224);
      uint32_t o0 = hmul2(dup_lo(pw.x), vw[n + 7]), o1 = hmul2(dup_hi(pw.x), vw[n + 6]);
      o0 = hfma2(dup_lo(pw.y), vw[n + 5], o0); o1 = hfma2(dup_hi(pw.y), vw[n + 4], o1);
      o0 = hfma2(dup_lo(pw.z), vw[n + 3], o0); o1 = hfma2(dup_hi(pw.z), vw[n + 2], o1);
      o0 = hfma2(dup_lo(pw.w), vw[n + 1], o0); o1 = hfma2(dup_hi(pw.w), vw[n], o1);
      o[n] = hadd2(o0, o1);
    }
    if (lane < 28) {
      #pragma unroll
      for (int m = 0; m < 4; m++)
        asm volatile("st.shared.v2.u32 [%0], {%1,%2};" :: "r"(oa + hb * 1792 + m * 8 * es), "r"((o[m] & mk1) | mk2), "r"(o[m + 4]) : "memory");
    }
  }
}

__device__ __forceinline__ void halo_put(uint4* dst, uint32_t src, int lane, uint32_t mark) {
  if (lane < 28) {
    #pragma unroll
    for (int k = 0; k < 4; k++) { const uint4 t = lds_v4(src + (lane + 28 * k) * 16); st_relaxed_128(dst + lane + 28 * k, (t.x & ~1u) | mark, t.y, t.z, t.w); }
  }
  __syncwarp();
}
__device__ __forceinline__ void halo_check(const uint4* src, uint32_t dst, int lane, bool have, uint32_t mark) {
  uint4 t[4];
  uint32_t cnt = 0;
  const bool act = have && lane < 28;
  #pragma unroll
  for (int k = 0; k < 4; k++) { t[k] = make_uint4(mark, 0u, 0u, 0u); if (act) t[k] = lds_v4(dst + (lane + 28 * k) * 16); }
  while (true) {
    bool bad = false;
    #pragma unroll
    for (int k = 0; k < 4; k++) bad |= (t[k].x & 1u) != mark;
    if (!__any_sync(0xffffffffu, bad)) break;
    #pragma unroll
    for (int k = 0; k < 4; k++) if (act) t[k] = ld_relaxed_128(src + lane + 28 * k);
    if (++cnt > SPIN_LIMIT) __trap();
  }
  if (lane < 28) {
    #pragma unroll
    for (int k = 0; k < 4; k++) sts_v4(dst + (lane + 28 * k) * 16, make_uint4(t[k].x & ~1u, t[k].y, t[k].z, t[k].w));
  }
  __syncwarp();
}

__device__ __forceinline__ void patch_store(Scratch* S, int lane, uint4 v0, uint4 v1, int dstA, int dstB) {
  if (lane & 4) { const uint4 t = v0; v0 = v1; v1 = t; }
  const int hi = lane & 4;
  const int sa = (lane & 3) * 8 + (lane >> 3) + hi, sbn = sa ^ 4;
  uint4 s1, s2;
  s1.x = __shfl_sync(0xffffffffu, v0.x, sa); s1.y = __shfl_sync(0xffffffffu, v0.y, sa); s1.z = __shfl_sync(0xffffffffu, v0.z, sa); s1.w = __shfl_sync(0xffffffffu, v0.w, sa);
  S->img[(hi ? dstB : dstA) + (lane & 7)] = s1;
  s2.x = __shfl_sync(0xffffffffu, v1.x, sbn); s2.y = __shfl_sync(0xffffffffu, v1.y, sbn); s2.z = __shfl_sync(0xffffffffu, v1.z, sbn); s2.w = __shfl_sync(0xffffffffu, v1.w, sbn);
  S->img[(hi ? dstA : dstB) + (lane & 7)] = s2;
}

__device__ __forceinline__ void fetch_u(Scratch* S, uint32_t sb, int cta, int b, uint32_t mark) {
  const int l8 = fresh_lane() & 7, lw = l8 >> 2;
  const uint32_t bar0 = sb + BAR_OFF;
  const unsigned* hp = &S->hint_u[cta][8 * b + l8];
  const uint32_t spb = bar0 + 8u * (uint32_t)(b == 0 ? B_GFREE + lw : (b == 1 ? B_WFREE : (lw ? B_WFREE + 1 : B_SPACE)));
  const uint4* src = S->ufrag + ((cta & ~7) + ((cta + 2 * (b + 1)) & 7)) * 1792;
  const uint32_t dst = sb + (b == 0 ? ub_off(0) : (b == 1 ? ub_off(1) : ub_off(2))), str = b < 2 ? ub_str(0) : ub_str(2);
  uint32_t todo = 0x11u, n = 0;
  unsigned h[NPOLL];
  bool have = false;
  mbar_wait(bar0 + 8u * B_GX, 0);
  #pragma unroll
  for (int k = 0; k < NPOLL; k++) { h[k] = ld_relaxed_32(hp); __nanosleep(POLLNS); }
  while (true) {
    #pragma unroll
    for (int k = 0; k < NPOLL; k++) {
      have |= h[k] == mark;
      uint32_t rdy = __ballot_sync(0xffffffffu, have && mbar_test(spb, 0));
      rdy &= rdy >> 2; rdy &= (rdy >> 1) & todo;
      todo &= ~rdy;
      if (rdy && elect_one()) {
        #pragma unroll
        for (int w = 0; w < 2; w++)
          if (rdy >> (4 * w) & 1) {
            mbar_expect_tx(bar0 + 8u * (uint32_t)(B_UF + 2 * b + w), 14336);
            bulk_g2s(dst + w * str, src + w * 896, 14336, bar0 + 8u * (uint32_t)(B_UF + 2 * b + w));
          }
      }
      __syncwarp();
      if (!todo) return;
      h[k] = ld_relaxed_32(hp);
      __nanosleep(POLLNS);
    }
    if (++n > SPIN_LIMIT) __trap();
  }
}

__global__ void __cluster_dims__(2, 1, 1) __launch_bounds__(384, 1)
fused_kernel(const __grid_constant__ CUtensorMap mX, const __grid_constant__ CUtensorMap mWin,
             const __grid_constant__ CUtensorMap mWsp, const __grid_constant__ CUtensorMap mXr,
             const __grid_constant__ CUtensorMap mOut, const Params p) {
  extern __shared__ __align__(1024) uint8_t smem_raw[];
  const uint32_t sb = smem_u32(smem_raw);
  const uint32_t bar0 = sb + BAR_OFF;
  auto BAR = [&](int k) { return bar0 + 8u * (uint32_t)k; };
  Scratch* const S = p.S;
  const int tid = threadIdx.x;
  const int warp = __shfl_sync(0xffffffffu, tid >> 5, 0);
  if (blockIdx.x < NSVC) {
    const int lane = tid & 31;
    #pragma unroll 1
    for (int k = 0; k < (25 + SVE - 1) / SVE; k++) {
      uint4 t4[SVE][2];
      #pragma unroll
      for (int e = 0; e < SVE; e++) {
        const int id = (blockIdx.x * 12 + warp) + 48 * (SVE * k + e), kg = id / 7, cb = id - 7 * kg;
        const __nv_bfloat16* src = (kg < 56 ? p.wo : p.wout - 448 * 448) + (kg * 8 + (lane >> 3)) * 448 + cb * 64 + (lane & 7) * 8;
        if (id < 1176) { t4[e][0] = ld_nc_v4(src); t4[e][1] = ld_nc_v4(src + 4 * 448); }
      }
      #pragma unroll
      for (int e = 0; e < SVE; e++) {
        const int id = (blockIdx.x * 12 + warp) + 48 * (SVE * k + e), kg = id / 7, cb = id - 7 * kg;
        const bool iswo = kg < 56;
        int khd, pos;
        const int rb = kg / 14 - 4;
        if (iswo) { khd = kg / 28; const int e28 = kg - 28 * khd, cl = e28 / 7, t7 = e28 - 7 * cl; pos = t7 < 6 ? cl * 6 + t7 : 24 + cl; }
        else { khd = rb & 1; pos = 28 + kg - 56 - 14 * rb; }
        int d[2];
        #pragma unroll
        for (int f = 0; f < 2; f++) {
          const int c8 = cb * 8 + (lane >> 3) + 4 * f, c7 = c8 / 7, cd = (c7 & 6) + khd;
          d[f] = cd * IMG_SZ + IMG_W3 + ((pos + (iswo ? 0 : 7 * ((rb - cd) & 7))) * 14 + (c7 == cd ? 0 : 7) + c8 - 7 * c7) * 8;
        }
        if (id < 1176) patch_store(S, lane, t4[e][0], t4[e][1], d[0], d[1]);
      }
    }
    __syncthreads();
    if (tid == 0) red_release(S->cnt_bg);
    return;
  }
  const int k_ = blockIdx.x >> 1;
  int r_, m_;
  if (k_ >= 4 && k_ < 36) { r_ = (k_ - 4) & 7; m_ = (k_ - 4) >> 3; }
  else if (k_ >= 36 && k_ < 64) { m_ = (k_ - 36) / 7; r_ = k_ - 36 - 7 * m_; m_ += 4; }
  else { r_ = 7; m_ = 4 + (k_ & 1) + ((k_ >> 6) << 1); }
  const int cta = (blockIdx.x & 1) | (r_ >> 2) << 1 | (m_ & 1) << 2 | (r_ & 3) << 3 | (m_ >> 1) << 5;
  const int i = cta >> 3, c = cta & 7, kh = c & 1;

  if (warp >= 8) {
    if (warp == 8 && elect_one()) {
      mbar_init(BAR(B_XF), 1);
      fence_async_smem();
      mbar_expect_tx(BAR(B_XF + 0), 7 * BOX1);
      tma_3d(sb + 14 * BOX1, &mX, 0, 128 * i, 0, BAR(B_XF + 0));
      asm volatile("prefetch.tensormap [%0];" :: "l"(&mWin) : "memory");
    }
    __syncwarp();
    asm volatile("setmaxnreg.dec.sync.aligned.u32 56;");
    if (warp == 8) {
      if (elect_one()) {
        if ((sb & 0x3FFFFu) != SB_LOW) __trap();
        #pragma unroll
        for (int k = 0; k < 7; k++) mbar_init(BAR(B_P1F + k), 1);
        mbar_init(BAR(B_XF + 1), 1);
        fence_async_smem();
      }
      __syncwarp();
      asm volatile("barrier.cluster.arrive.relaxed.aligned;" ::: "memory");
      bar_arrive(6, 384);
      if (elect_one()) {
        TSTAMP(2, 16);
        const int cz = c < 7 ? c : 6;
        #pragma unroll
        for (int kc = 0; kc < 7; kc++) {
          if (kc == XORDER) {
            mbar_expect_tx(BAR(B_XF + 1), 7 * BOX1);
            tma_3d(sb + 21 * BOX1, &mX, 0, 128 * i + 64, 0, BAR(B_XF + 1));
          }
          mbar_expect_tx(BAR(B_P1F + kc), 2 * BOX1);
          tma_3d(sb + 2 * kc * BOX1, &mWin, 0, 64 * kc, 14 + 2 * cz, BAR(B_P1F + kc));
        }
        TSTAMP(2, 20);
      }
      __syncwarp();
      const unsigned epoch = ld_u32_lazy(&S->epoch[cta]) + 1u;
      const uint4* img = S->img + c * IMG_SZ;
      const uint8_t* pf = reinterpret_cast<const uint8_t*>(p.wsp) + cta * 65536;
      asm volatile("barrier.cluster.wait.aligned;" ::: "memory");
      if (elect_one()) {
        wait_cnt(S->cnt_p2, epoch * 128u);
        fence_async_global();
        TSTAMP(2, 8);
        mbar_wait(BAR(B_XE), 0);
        #pragma unroll
        for (int s = 0; s < 7; s++) {
          if (s >= 4) mbar_wait(BAR(B_P1E + s - 4), 0);
          mbar_expect_tx(BAR(B_P1F + 7 + s), P2ST);
          bulk_g2s(sb + p2_off(s), img + IMG_P2 + s * (P2ST / 16), P2ST, BAR(B_P1F + 7 + s));
          if (s >= 3) l2_prefetch(pf + (s - 3) * 6144, 6144);
        }
        wait_cnt(S->cnt_p3, epoch * 128u);
        fence_async_global();
        TSTAMP(2, 10);
        #pragma unroll
        for (int s = 0; s < 7; s++) {
          mbar_wait(BAR(B_P1E + ((0xCA98654u >> (4 * s)) & 15)), 0);
          mbar_expect_tx(BAR(B_P1F + 14 + s), P3ST);
          bulk_g2s(sb + p3_off(s), img + IMG_P3 + s * (P3ST / 16), P3ST, BAR(B_P1F + 14 + s));
          if (s >= 2) l2_prefetch(pf + 24576 + (s - 2) * 8192, 8192);
        }
        TSTAMP(2, 0);
        const unsigned zt = epoch * ((c >> 1) == 0 || (c >> 1) == 3 ? 16u : 24u);
        wait_cnt(S->cnt_z2[kh * 8 + (c >> 1)], zt);
        fence_async_global();
        TSTAMP(2, 1);
        unsigned zv = 0;
        #pragma unroll 1
        for (int it = 0; it < 14; it++) {
          const unsigned* cp = it < 11 ? S->cnt_z2[(it < 8 ? kh : kh ^ 1) * 8 + 4 + (c >> 1)] : S->cnt_bg;
          if (it == 7 || it == 10 || it == 13) {
            const unsigned want = it < 11 ? zt : epoch * (unsigned)NSVC;
            if (zv != want) wait_cnt(cp, want);
            fence_async_global();
            if (it == 13) { mbar_arrive(BAR(B_ORDY)); TSTAMP(2, 11); }
          }
          if (it == 4 || it == 8 || it == 11) zv = ld_relaxed_32(cp);
          mbar_wait(it < 4 ? BAR(B_P1E + (it == 3 ? 20 : 15 + 2 * it)) : BAR(B_P2E + (it & 3)), it < 4 ? 0 : ((it >> 2) - 1) & 1);
          const uint32_t st = sb + (uint32_t)((it + 1) & 3) * STAGE2, fb = BAR(B_P2F + (it & 3));
          const int kb = 16 * kh + 2 * (it & 7) + (it >> 3);
          mbar_expect_tx(fb, STAGE2);
          tma_2d(st, &mWsp, kb * 64, 128 * i, fb);
          bulk_g2s(st + 16384, S->z2t + (kb * 8 + c) * 896, ZBLK, fb);
          bulk_g2s(st + 16384 + ZBLK, S->z2t + (kb * 8 + (c ^ 1)) * 896, ZBLK, fb);
        }
        #pragma unroll
        for (int e = 0; e < 4; e++) {
          if (e < 3) mbar_wait(BAR(B_P2E + ((e + 2) & 3)), e >> 1);
          const uint32_t fb = BAR(B_P2F + ((e + 2) & 3));
          const int kb = 13 + 2 * (e & 1) + 16 * (e >> 1);
          mbar_expect_tx(fb, 16384 + ZBLK);
          tma_2d(sb + sa_off(e), &mWsp, kb * 64, 128 * i, fb);
          bulk_g2s(sb + sz_off(e), S->z2t + (kb * 8 + c) * 896, ZBLK, fb);
        }
        TSTAMP(2, 2);
        #pragma unroll
        for (int b = 0; b < 4; b++) {
          if (b < 2) mbar_wait(BAR(B_P2E + 2 + b), 1);
          mbar_expect_tx(BAR(B_P3F + b), W3BLK);
          bulk_g2s(sb + w3_off(b), img + IMG_W3 + (b == 0 ? 2 : (b < 3 ? b - 1 : b)) * (W3BLK / 16), W3BLK, BAR(B_P3F + b));
        }
        TSTAMP(2, 3);
      }
      __syncwarp();
    } else {
      const int hw = warp - 9;
      if (hw == 0 && elect_one()) {
        mbar_init(BAR(B_ZFREE), 1); mbar_init(BAR(B_ZFREE + 1), 1); mbar_init(BAR(B_RP2), 2);
        mbar_init(BAR(B_HK), 1); mbar_init(BAR(B_HV), 1);
        sts_u32(sb + CNT_OFF, 0);
        asm volatile("fence.mbarrier_init.release.cluster;" ::: "memory");
        fence_async_smem();
      }
      if (hw == 1 && elect_one()) {
        #pragma unroll
        for (int k = 0; k < 7; k++) mbar_init(BAR(B_OF + k), 1);
        mbar_init(BAR(B_SPACE), 8); mbar_init(BAR(B_WFREE), 2); mbar_init(BAR(B_WFREE + 1), 2);
                mbar_init(BAR(B_GFREE), 4); mbar_init(BAR(B_GFREE + 1), 4);
        asm volatile("fence.mbarrier_init.release.cluster;" ::: "memory");
        fence_async_smem();
      }
      __syncwarp();
      asm volatile("barrier.cluster.arrive.relaxed.aligned;" ::: "memory");
      bar_sync(6, 384);
      if (hw != 0) {
        LANE_VARS;
        mbar_wait(BAR(B_XF), 0);
        {
          uint4 rq[RPS][2];
          #pragma unroll
          for (int s = 0; s < RPS; s++) {
            const int id = cta * 2 + hw - 1 + 256 * s, kg = id / 21, cb = id - 21 * kg;
            const int pitch = cb < 7 ? 1344 : 1792;
            const __nv_bfloat16* src = (cb < 7 ? p.wqkv + 896 : p.win - 448) + (kg * 8 + lm) * pitch + cb * 64 + lr * 8;
            if (id < 1176) { rq[s][0] = ld_nc_v4(src); rq[s][1] = ld_nc_v4(src + 4 * pitch); }
          }
          int id0 = cta * 2 + hw - 1;
          asm volatile("" : "+r"(id0));
          #pragma unroll
          for (int s = 0; s < RPS; s++) {
            const int id = id0 + 256 * s, kg = id / 21, cb = id - 21 * kg;
            int d[2];
            #pragma unroll
            for (int e = 0; e < 2; e++) {
              const int c8 = cb * 8 + lm + 4 * e, g = c8 / 7;
              d[e] = (g < 8 ? g : (g - 8) >> 1) * IMG_SZ + IMG_P3 + kg * 168 + (g < 8 ? 112 : (g & 1) * 56) + (c8 - 7 * g) * 8;
            }
            if (id < 1176) patch_store(S, lane, rq[s][0], rq[s][1], d[0], d[1]);
          }
        }
        __syncwarp();
        if (lane == 0) { mbar_arrive(BAR(B_RP2)); TSTAMP(2, 23); }
      }
      const unsigned epoch = ld_u32_lazy(&S->epoch[cta]) + 1u;
      if (hw == 0) {
        const int lane = fresh_lane();
        mbar_wait(BAR(B_RP), 0);
        if (lane == 0) { red_release(S->cnt_p2); TSTAMP(2, 9); }
        mbar_wait(BAR(B_RP2), 0);
        if (elect_one()) {
          red_release(S->cnt_p3); TSTAMP(2, 28);
        }
        __syncwarp();
        const uint32_t tag0 = epoch & 15u, tag1 = (epoch >> 4) & 15u;
        #pragma unroll 1
        for (int w = 0; w < 2; w++) {
          mbar_wait(BAR(B_P1E + (w ? 9 : 4)), 0);
          const uint2* sp = &S->stats[(128 * i + 64 * w + lane) * 8];
          uint4 e[8];
          uint32_t n = 0;
          while (true) {
            uint32_t bad = 0;
            #pragma unroll
            for (int k = 0; k < 8; k++) e[k] = ld_relaxed_2x64(sp + (k >> 2) * 256 + (k & 3) * 2);
            #pragma unroll
            for (int k = 0; k < 8; k++) {
              bad |= (e[k].x ^ tag0) | (e[k].y ^ tag1);
              if ((k & 3) != 3) bad |= (e[k].z ^ tag0) | (e[k].w ^ tag1);
            }
            if (__all_sync(0xffffffffu, (bad & 15u) == 0)) break;
            if (++n > SPIN_LIMIT) __trap();
          }
          #pragma unroll
          for (int h = 0; h < 2; h++) {
            float su = __uint_as_float(e[4 * h + 3].x), sq = __uint_as_float(e[4 * h + 3].y);
            #pragma unroll
            for (int k = 0; k < 3; k++) {
              su += __uint_as_float(e[4 * h + k].x) + __uint_as_float(e[4 * h + k].z);
              sq += __uint_as_float(e[4 * h + k].y) + __uint_as_float(e[4 * h + k].w);
            }
            const float mean = su * (1.0f / 896.0f);
            const float rstd = rsqrtf(fmaxf(sq * (1.0f / 896.0f) - mean * mean, 0.f) + 1e-5f);
            const uint32_t rp2 = pack_bf16(rstd, rstd);
            const float bia = -mean * bf_lo(rp2);
            asm volatile("st.shared.v2.u32 [%0], {%1,%2};" :: "r"(sb + NB_OFF + (64 * w + 32 * h + lane) * 8), "r"(rp2), "r"(pack_bf16(bia, bia)) : "memory");
          }
          __syncwarp();
          if (lane == 0) { mbar_arrive(BAR(B_ST + w)); TSTAMP(2, 25 + w); }
        }
        mbar_wait(BAR(B_QK + 1), 0);
        if (i < 15) halo_put(S->halo + (cta + 8) * 256, sb + K_OFF + 128 * 112, lane, epoch & 1u);
      } else if (hw == 2) {
        const int lane = fresh_lane();
        if (elect_one()) {
          #pragma unroll 1
          for (int w = 0; w < 2; w++) {
            mbar_wait(BAR(B_ZFULL), w);
            if (c < 7) bulk_s2g(S->z2t + (2 * i + w) * 7168 + c * 1024, sb + V_OFF, 16384);
            asm volatile("cp.async.bulk.commit_group;" ::: "memory");
            asm volatile("cp.async.bulk.wait_group.read 0;" ::: "memory");
            mbar_arrive(BAR(B_ZFREE + w));
            asm volatile("cp.async.bulk.wait_group 0;" ::: "memory");
            asm volatile("fence.acq_rel.gpu;" ::: "memory");
            if (c < 7) {
              red_relaxed(S->cnt_z2[(i >> 3) * 8 + w * 4 + (c >> 1)]);
              if (c & 1) red_relaxed(S->cnt_z2[(i >> 3) * 8 + w * 4 + (c >> 1) + 1]);
            }
            TSTAMP(2, 4 + w);
          }
        }
        __syncwarp();
        mbar_wait(BAR(B_V + 1), 0);
        if (i < 15) halo_put(S->halo + (cta + 8) * 256 + 128, sb + V_OFF + 128 * 112, lane, epoch & 1u);
        if (elect_one()) TSTAMP(2, 27);
      }
      #pragma unroll 1
      while (true) {
        const int lane = fresh_lane();
        uint32_t t = 0;
        if (lane == 0) asm volatile("atom.shared.add.u32 %0, [%1], 1;" : "=r"(t) : "r"(sb + CNT_OFF) : "memory");
        t = __shfl_sync(0xffffffffu, t, 0);
        if (t > 7) break;
        mbar_wait(BAR(B_QK + 0), 0);
        if (t >= 3) mbar_wait(BAR(B_QK + 1), 0);
        if (t == 3 || t == 7) {
          if (elect_one()) {
            mbar_wait(BAR(B_ZFREE + 1), 0);
            const uint32_t hb = t == 3 ? BAR(B_HK) : BAR(B_HV);
            mbar_expect_tx(hb, 1792);
            bulk_g2s(sb + (t == 3 ? K_OFF : V_OFF), S->halo + cta * 256 + (t == 3 ? 0 : 128), 1792, hb);
          }
          __syncwarp();
        }
        if (t == G0T) { mbar_wait(BAR(B_HK), 0); halo_check(S->halo + cta * 256, sb + K_OFF, lane, i > 0, epoch & 1u); }
        attn_scores(sb, t == G0T ? 0 : (t < G0T ? t + 1 : t), lane, i);
      }
      if (elect_one()) TSTAMP(2, 12 + hw);
      mbar_wait(BAR(B_V + 0), 0); mbar_wait(BAR(B_V + 1), 0);
      bar_sync(3, 96);
      #pragma unroll 1
      for (int n = 0; n < 3; n++) {
        if (hw == 2 && n == 0) { mbar_wait(BAR(B_HV), 0); halo_check(S->halo + cta * 256 + 128, sb + V_OFF, fresh_lane(), i > 0, epoch & 1u); continue; }
        attn_pv(sb, hw == 2 ? 0 : 1 + n, hw == 2 ? n - 1 : hw, fresh_lane(), epoch & 1u);
      }
      fence_async_smem();
      bar_sync(3, 96);
      asm volatile("barrier.cluster.wait.aligned;" ::: "memory");
      if (elect_one()) {
        TSTAMP(2, 7);
        if (hw == 2) {
          bulk_s2g(S->ofrag + cta * 896, sb + K_OFF, 14336);
          asm volatile("cp.async.bulk.commit_group;" ::: "memory");
          asm volatile("cp.async.bulk.wait_group.read 0;" ::: "memory");
          mbar_arrive_remote(mapa(BAR(B_PEERQ), kh ^ 1));
          S->epoch[cta] = epoch;
          asm volatile("cp.async.bulk.wait_group 0;" ::: "memory");
          red_relaxed(S->hint_o[2 * i + (c >> 2)]);
          TSTAMP(2, 6);
        }
        if (hw == 1) {
          wait_hint(S->hint_o[2 * i + kh], epoch * 4u);
          TSTAMP(2, 15);
          mbar_wait(BAR(B_ORDY), 0);
          mbar_wait(BAR(B_P2E + 0), 1);
          mbar_expect_tx(BAR(B_OF), 4 * 14336);
          bulk_g2s(sb + OB_OFF, S->ofrag + (8 * i + 4 * kh) * 896, 12288, BAR(B_OF));
          mbar_wait(BAR(B_P2E + 1), 1);
          bulk_g2s(sb + OB_OFF + 12288, S->ofrag + (8 * i + 4 * kh) * 896 + 768, STAGE2, BAR(B_OF));
        }
        if (hw == 0) {
          mbar_wait(BAR(B_ORDY), 0);
          fence_async_global();
          mbar_wait(BAR(B_SPACE), 0);
          #pragma unroll
          for (int e = 0; e < 2; e++) {
            mbar_expect_tx(BAR(B_P3F + 4 + e), W3BLK);
            bulk_g2s(sb + w3_off(4 + e), S->img + c * IMG_SZ + IMG_W3 + (4 + e) * (W3BLK / 16), W3BLK, BAR(B_P3F + 4 + e));
          }
          mbar_wait(BAR(B_RP2), 1);
          mbar_expect_tx(BAR(B_HK), 128 * 112);
          tma_2d(sb + XO_OFF, &mXr, 56 * c, 128 * i, BAR(B_HK));
        }
      }
      __syncwarp();
    }
    if (warp != 9) {
      const uint32_t mark = lds_u32(sb + CNT_OFF + 4);
      fetch_u(S, sb, cta, warp == 8 ? 0 : warp - 9, mark);
      if (warp == 8 && elect_one()) TSTAMP(2, 29);
    }
  } else {
    uint4 rp[2][2];
    if (warp >= 4) {
      LANE_VARS;
      #pragma unroll
      for (int s = 0; s < 2; s++) {
        const int id = cta * 4 + (warp - 4) + 512 * s, kg = id / 14, cb = id - 14 * kg;
        const __nv_bfloat16* src = p.wqkv + (kg * 8 + lm) * 1344 + cb * 64 + lr * 8;
        if (id < 784) { rp[s][0] = ld_nc_v4(src); rp[s][1] = ld_nc_v4(src + 4 * 1344); }
      }
    } else if (elect_one()) {
      #pragma unroll
      for (int k = 0; k < 8; k++) mbar_init(BAR(7 + 8 * warp + k), 1);
      #pragma unroll
      for (int k = 0; k < 8; k++) mbar_init(BAR(B_P1E + 8 * warp + k), warp < 3 || k == 0 ? 2 : 4);
      if (warp == 3) {
        mbar_expect_tx(BAR(B_GX), 128 * 112); mbar_expect_tx(BAR(B_GX + 1), 128 * 112);
        mbar_expect_tx(BAR(B_FX), 128 * 56); mbar_expect_tx(BAR(B_FX + 1), 128 * 56);
      }
      asm volatile("fence.mbarrier_init.release.cluster;" ::: "memory");
      fence_async_smem();
    }
    __syncwarp();
    asm volatile("barrier.cluster.arrive.relaxed.aligned;" ::: "memory");
    bar_sync(6, 384);
    asm volatile("setmaxnreg.inc.sync.aligned.u32 224;");
    const int w = warp >> 2, v = warp & 3;
    const int rowb = 128 * i + 16 * warp;
    const bool lead = (tid & 127) == 0, lane0 = (tid & 31) == 0;
    if (lead) TSTAMP(w, 16);
    if (w == 1) {
      LANE_VARS;
      #pragma unroll
      for (int s = 0; s < 2; s++) {
        const int id = cta * 4 + v + 512 * s, kg = id / 14, cb = id - 14 * kg;
        int d[2];
        #pragma unroll
        for (int e = 0; e < 2; e++) {
          const int c8 = cb * 8 + lm + 4 * e, g = c8 / 7;
          d[e] = (g & 7) * IMG_SZ + IMG_P2 + kg * 112 + (g >> 3) * 56 + (c8 - 7 * g) * 8;
        }
        if (id < 784) patch_store(S, lane, rp[s][0], rp[s][1], d[0], d[1]);
      }
      __syncwarp();
      if (lane == 0) mbar_arrive(BAR(B_RP));
      if (lead) TSTAMP(2, 24);
    }
    uint32_t a[28][4];
    float dm0, dm1;
    uint32_t mm0, mm1;
    {
      LANE_VARS;
      const uint32_t ro = sb + (uint32_t)(16 * v + (lm & 1) * 8 + lr) * 128;
      const uint32_t xb = ro + (14 + 7 * w) * BOX1;
      mbar_wait(BAR(B_XF + w), 0);
      if (lead) TSTAMP(w, 17);
      #pragma unroll
      for (int ks = 0; ks < 28; ks++) {
        const uint32_t ch = (uint32_t)(((2 * (ks & 3) + (lm >> 1)) ^ lr) * 16);
        ldsm_x4(xb + (ks >> 2) * BOX1 + ch, a[ks][0], a[ks][1], a[ks][2], a[ks][3]);
      }
      float m0 = 0.f, m1 = 0.f;
      #pragma unroll
      for (int kc = 0; kc < 7; kc++) {
        uint32_t t[2];
        #pragma unroll
        for (int e = 0; e < 2; e++)
          t[e] = hadd2(hadd2(hadd2(a[4 * kc][e], a[4 * kc][e + 2]), hadd2(a[4 * kc + 1][e], a[4 * kc + 1][e + 2])),
                       hadd2(hadd2(a[4 * kc + 2][e], a[4 * kc + 2][e + 2]), hadd2(a[4 * kc + 3][e], a[4 * kc + 3][e + 2])));
        m0 += bf_lo(t[0]) + bf_hi(t[0]); m1 += bf_lo(t[1]) + bf_hi(t[1]);
      }
      m0 = quad_sum(m0) * (1.0f / 448.0f); m1 = quad_sum(m1) * (1.0f / 448.0f);
      if (w == 0 && lane0) mbar_arrive(BAR(B_XE));
      mm0 = pack_bf16(m0, m0); mm1 = pack_bf16(m1, m1);
      dm0 = m0 - bf_lo(mm0); dm1 = m1 - bf_lo(mm1);
    }
    if (lead) TSTAMP(w, 0);
    uint32_t zp[32];
    {
      float acc[64];
      float v0 = 0.f, v1 = 0.f;
      auto centre = [&](int kc) {
        uint32_t t0 = 0u, t1 = 0u;
        #pragma unroll
        for (int e = 0; e < 8; e++) {
          uint32_t& e0 = a[4 * kc + (e >> 1)][(e & 1) * 2];
          uint32_t& e1 = a[4 * kc + (e >> 1)][(e & 1) * 2 + 1];
          e0 = hsub2(e0, mm0); e1 = hsub2(e1, mm1);
          t0 = e ? hfma2(e0, e0, t0) : hmul2(e0, e0); t1 = e ? hfma2(e1, e1, t1) : hmul2(e1, e1);
        }
        v0 += bf_lo(t0) + bf_hi(t0); v1 += bf_lo(t1) + bf_hi(t1);
      };
      centre(0);
      #pragma unroll
      for (int kc = 0; kc < 7; kc++) {
        mbar_wait(BAR(B_P1F + kc), 0);
        wgmma_fence();
        #pragma unroll
        for (int k = 0; k < 4; k++) {
          const int ks = kc * 4 + k;
          wgmma_rt_n128(acc, a[ks][0], a[ks][1], a[ks][2], a[ks][3], mk_desc((2 * kc) * BOX1 + k * 2048, BOX1, 1024), ks != 0);
        }
        wgmma_commit();
        if (kc < 6) centre(kc + 1);
        if (kc > 0) { wgmma_wait<1>(); if (lead && !(v0 + v1 < 0.f)) mbar_arrive(BAR(B_P1E + kc - 1)); }
      }
      if (w) bar_arrive(1, 256);
      LANE_VARS;
      const unsigned epoch = ld_u32_lazy(&S->epoch[cta]) + 1u;
      const float rs0 = rsqrtf(fmaxf(quad_sum(v0) * (1.0f / 448.0f) - dm0 * dm0, 0.f) + 1e-5f);
      const float rs1 = rsqrtf(fmaxf(quad_sum(v1) * (1.0f / 448.0f) - dm1 * dm1, 0.f) + 1e-5f);
      if (q < 2) sts_u32(sb + RS_OFF + (uint32_t)(16 * warp + rr + 8 * q) * 4, __float_as_uint(q ? rs1 : rs0));
      const float gh0 = 0.5f * rs0, gh1 = 0.5f * rs1, g10 = 0.7978845608f * rs0, g11 = 0.7978845608f * rs1;
      const float g20 = 0.0356774081f * rs0 * rs0 * rs0, g21 = 0.0356774081f * rs1 * rs1 * rs1;
      wgmma_wait<0>();
      if (lead) { mbar_arrive(BAR(B_P1E + 6)); TSTAMP(w, 1); }
      float s0 = 0.f, s1 = 0.f, q0 = 0.f, q1 = 0.f;
      #pragma unroll
      for (int nt = 0; nt < 16; nt++) {
        const float e0 = gelu_s(acc[4 * nt], g10, g20, gh0), e1 = gelu_s(acc[4 * nt + 1], g10, g20, gh0);
        const float e2 = gelu_s(acc[4 * nt + 2], g11, g21, gh1), e3 = gelu_s(acc[4 * nt + 3], g11, g21, gh1);
        s0 += e0 + e1; s1 += e2 + e3;
        q0 = fmaf(e0, e0, fmaf(e1, e1, q0)); q1 = fmaf(e2, e2, fmaf(e3, e3, q1));
        zp[2 * nt] = pack_bf16(e0, e1); zp[2 * nt + 1] = pack_bf16(e2, e3);
      }
      s0 = quad_sum(s0); s1 = quad_sum(s1); q0 = quad_sum(q0); q1 = quad_sum(q1);
      sts_u32(sb + CNT_OFF + 4, epoch & 1u);
      if (q < 2)
        st_relaxed_64(&S->stats[(rowb + rr + 8 * q) * 8 + c], (__float_as_uint(q ? s1 : s0) & ~15u) | (epoch & 15u),
                      (__float_as_uint(q ? q1 : q0) & ~15u) | ((epoch >> 4) & 15u));
    }
    if (lead) TSTAMP(w, 2);

    {
      float aq[56];
      bar_sync(1 + w, 256);
      #pragma unroll
      for (int kc = 0; kc < 7; kc++) {
        mbar_wait(BAR(B_P1F + 7 + kc), 0);
        wgmma_fence();
        #pragma unroll
        for (int k = 0; k < 4; k++) {
          const int ks = kc * 4 + k;
          wgmma_rt_n112(aq, a[ks][0], a[ks][1], a[ks][2], a[ks][3], mk_desc_ns(p2_off(kc) + k * 3584, 112), ks != 0);
        }
        wgmma_commit();
        if (kc > 0) { wgmma_wait<1>(); if (lead) mbar_arrive(BAR(B_P1E + 7 + kc - 1)); }
      }
      bar_arrive(1 + (w ^ 1), 256);
      wgmma_wait<0>();
      if (lead) { mbar_arrive(BAR(B_P1E + 13)); TSTAMP(w, 18); }
      LANE_VARS;
      const uint32_t tile_ro = (uint32_t)(16 * warp + (lm & 1) * 8 + lr) * 112;
      const float rs0 = __uint_as_float(lds_u32(sb + RS_OFF + (uint32_t)(16 * warp + rr) * 4)), rs1 = __uint_as_float(lds_u32(sb + RS_OFF + (uint32_t)(8 + 16 * warp + rr) * 4));
      {
        uint32_t pq[28];
        #pragma unroll
        for (int n = 0; n < 28; n++) {
          const float f = n < 14 ? 1.0f : ((n & 1) ? rs1 : rs0);
          pq[n] = pack_bf16(aq[2 * n] * f, aq[2 * n + 1] * f);
        }
        const uint32_t qa = sb + Q_OFF + tile_ro, ka = sb + K_OFF + 16 * 112 + tile_ro;
        #pragma unroll
        for (int np = 0; np < 3; np++) {
          stsm_x4(qa + (lm >> 1) * 16 + np * 32, pq[4 * np], pq[4 * np + 1], pq[4 * np + 2], pq[4 * np + 3]);
          stsm_x4(ka + (lm >> 1) * 16 + np * 32, pq[14 + 4 * np], pq[14 + 4 * np + 1], pq[14 + 4 * np + 2], pq[14 + 4 * np + 3]);
        }
        stsm_x4((lm >> 1 ? ka : qa) + 96, pq[12], pq[13], pq[26], pq[27]);
        __syncwarp();
        if (lane0) mbar_arrive(BAR(B_QK + w));
      }
      mbar_wait(BAR(B_ST + w), 0);
      if (lead) TSTAMP(w, 3);
      const uint2 n0 = lds_v2(sb + NB_OFF + (uint32_t)(16 * warp + rr) * 8), n1 = lds_v2(sb + NB_OFF + (uint32_t)(16 * warp + rr + 8) * 8);
      if (w == 1) mbar_wait(BAR(B_ZFREE), 0);
      const uint32_t zb = sb + V_OFF + (uint32_t)((lm >> 1) * 8 + lr) * 128 + (uint32_t)(((2 * v + (lm & 1)) ^ lr) * 16);
      #pragma unroll
      for (int np = 0; np < 8; np++)
        stsm_x4_t(zb + np * 2048, hfma2(zp[4 * np], n0.x, n0.y), hfma2(zp[4 * np + 1], n1.x, n1.y), hfma2(zp[4 * np + 2], n0.x, n0.y), hfma2(zp[4 * np + 3], n1.x, n1.y));
      fence_async_smem();
      __syncwarp();
      if (lane0) mbar_arrive(BAR(B_ZFULL));
    }
    if (lead) TSTAMP(w, 4);

    uint32_t z1p[28];
    {
      float acc[84];
      bar_sync(1 + w, 256);
      #pragma unroll
      for (int kc = 0; kc < 7; kc++) {
        mbar_wait(BAR(B_P1F + 14 + kc), 0);
        wgmma_fence();
        #pragma unroll
        for (int k = 0; k < 4; k++) {
          const int ks = kc * 4 + k;
          wgmma_rt_n168(acc, a[ks][0], a[ks][1], a[ks][2], a[ks][3], mk_desc_ns(p3_off(kc) + k * 5376, 168), ks != 0);
        }
        wgmma_commit();
        if (kc > 0) { wgmma_wait<1>(); if (lead) mbar_arrive(BAR(B_P1E + 14 + kc - 1)); }
      }
      if (w == 0) bar_arrive(2, 256);
      LANE_VARS2;
      const uint32_t tile_ro = (uint32_t)(16 * warp + (lm & 1) * 8 + lr) * 112;
      const float rs0 = __uint_as_float(lds_u32(sb + RS_OFF + (uint32_t)(16 * warp + rr) * 4)), rs1 = __uint_as_float(lds_u32(sb + RS_OFF + (uint32_t)(8 + 16 * warp + rr) * 4));
      const float gh0 = 0.5f * rs0, gh1 = 0.5f * rs1, g10 = 0.7978845608f * rs0, g11 = 0.7978845608f * rs1;
      const float g20 = 0.0356774081f * rs0 * rs0 * rs0, g21 = 0.0356774081f * rs1 * rs1 * rs1;
      wgmma_wait<0>();
      if (lead) { mbar_arrive(BAR(B_P1E + 20)); TSTAMP(w, 5); }
      uint32_t pv[14];
      #pragma unroll
      for (int n = 0; n < 14; n++) pv[n] = pack_bf16(acc[56 + 2 * n] * ((n & 1) ? rs1 : rs0), acc[57 + 2 * n] * ((n & 1) ? rs1 : rs0));
      mbar_wait(BAR(B_ZFREE + 1), 0);
      const uint32_t va = sb + V_OFF + 16 * 112 + tile_ro;
      #pragma unroll
      for (int np = 0; np < 3; np++) stsm_x4(va + (lm >> 1) * 16 + np * 32, pv[4 * np], pv[4 * np + 1], pv[4 * np + 2], pv[4 * np + 3]);
      stsm_x2(va + 96, pv[12], pv[13]);
      __syncwarp();
      if (lane0) mbar_arrive(BAR(B_V + w));
      #pragma unroll
      for (int nt = 0; nt < 14; nt++) {
        z1p[2 * nt] = pack_bf16(gelu_s(acc[4 * nt], g10, g20, gh0), gelu_s(acc[4 * nt + 1], g10, g20, gh0));
        z1p[2 * nt + 1] = pack_bf16(gelu_s(acc[4 * nt + 2], g11, g21, gh1), gelu_s(acc[4 * nt + 3], g11, g21, gh1));
      }
    }
    if (lead) TSTAMP(w, 6);

    float acc[112];
    uint32_t bs0, bs1, mark;
    {
      const unsigned short* bp = reinterpret_cast<const unsigned short*>(p.bsp) + rowb + (fresh_lane2() >> 2);
      bs0 = __ldg(bp); bs1 = __ldg(bp + 8);
      mark = lds_u32(sb + CNT_OFF + 4);
    }
    #pragma unroll 1
    for (int it = 0; it < 14; it++) {
      mbar_wait(BAR(B_P2F + (it & 3)), (it >> 2) & 1);
      const uint32_t st = (uint32_t)((it + 1) & 3) * STAGE2;
      const uint64_t da = mk_desc(st + w * 8192, 16, 1024), db = mk_desc(st + 16384, 16, 1024);
      wgmma_fence();
      #pragma unroll
      for (int k = 0; k < 4; k++) wgmma_ss_n224<0, 0>(acc, da + 2 * k, db + 2 * k, (it | k) != 0);
      wgmma_commit();
      if (it > 0) { wgmma_wait<1>(); if (lead) mbar_arrive(BAR(B_P2E + ((it - 1) & 3))); }
    }
    auto short_stage = [&](int e) {
      mbar_wait(BAR(B_P2F + ((e + 2) & 3)), e < 2);
      wgmma_fence();
      const uint64_t da = mk_desc(sa_off(e), 16, 1024) + w * 512;
      #pragma unroll
      for (int k = 0; k < 4; k++) wgmma_ss_n112<0, 0>(acc, da + 2 * k, mk_desc(sz_off(e), 16, 1024) + 2 * k, 1);
      wgmma_commit();
    };
    short_stage(0);
    wgmma_wait<1>();
    if (lead) { mbar_arrive(BAR(B_P2E + 1)); TSTAMP(w, 13); }
    short_stage(1);
    LANE_VARS;
    asm volatile("barrier.cluster.wait.aligned;" ::: "memory");
    mbar_wait_cluster(BAR(B_PEERQ), 0);
    bs0 *= 0x10001u; bs1 *= 0x10001u;
    const int t128 = v * 32 + lane;
    const uint32_t gbuf = sb + Q_OFF + (uint32_t)warp * 3584 + lane * 16;
    {
      const uint32_t rbuf = mapa(gbuf, kh ^ 1), rbar = mapa(BAR(B_GX + w), kh ^ 1);
      #pragma unroll
      for (int k = 0; k < 7; k++) {
        const float* s = &acc[56 + 8 * k];
        st_async_v4(rbuf + k * 512, pack_bf16(s[0], s[1]), pack_bf16(s[2], s[3]), pack_bf16(s[4], s[5]), pack_bf16(s[6], s[7]), rbar);
        if (k == SPL) { short_stage(2); short_stage(3); }
        if (k == SPL2) { wgmma_wait<2>(); if (lead) mbar_arrive(BAR(B_P2E + 2)); }
      }
    }
    if (lead) TSTAMP(w, 14);
    float c3[56];
    {
      uint32_t of[14][4];
      auto load_o = [&]() {
        const uint32_t ob = sb + OB_OFF + warp * 1792;
        #pragma unroll
        for (int st = 0; st < 12; st++) { const uint4 t = lds_v4(ob + (st / 3) * 14336 + (st % 3) * 512 + lane * 16); of[st][0] = t.x; of[st][1] = t.y; of[st][2] = t.z; of[st][3] = t.w; }
        #pragma unroll
        for (int cl = 0; cl < 4; cl++) { const uint2 t = lds_v2(ob + cl * 14336 + 1536 + lane * 8); of[12 + cl / 2][(cl & 1) * 2] = t.x; of[12 + cl / 2][(cl & 1) * 2 + 1] = t.y; }
        __syncwarp();
        if (lane0 && (of[0][0] | of[13][3] | 1u)) mbar_arrive(BAR(B_SPACE));
        if (lead) TSTAMP(w, 19);
      };
      const bool early = __all_sync(0xffffffffu, mbar_test(BAR(B_OF), 0));
      if (early) load_o();
      wgmma_wait<0>();
      if (lead) { mbar_arrive(BAR(B_P2E + 3)); TSTAMP(w, 7); }
      uint32_t uf[7][4];
      #pragma unroll
      for (int n = 0; n < 28; n++) uf[n >> 2][n & 3] = pack_bf16(acc[2 * n], acc[2 * n + 1]);
      mbar_wait_cluster(BAR(B_GX + w), 0);
      if (lead) TSTAMP(w, 8);
      uint4* up = S->ufrag + (cta * 8 + warp) * 224 + lane;
      #pragma unroll
      for (int k = 0; k < 7; k++) {
        const uint4 rv = lds_v4(gbuf + k * 512);
        uf[k][0] = (hmul2(hadd2(hadd2(uf[k][0], rv.x), bs0), z1p[4 * k]) & ~1u) | mark;
        uf[k][1] = hmul2(hadd2(hadd2(uf[k][1], rv.y), bs1), z1p[4 * k + 1]);
        uf[k][2] = hmul2(hadd2(hadd2(uf[k][2], rv.z), bs0), z1p[4 * k + 2]);
        uf[k][3] = hmul2(hadd2(hadd2(uf[k][3], rv.w), bs1), z1p[4 * k + 3]);
        st_relaxed_128(up + k * 32, uf[k][0], uf[k][1], uf[k][2], uf[k][3]);
      }
      __syncwarp();
      if (lane < 3) st_relaxed_32(&S->hint_u[8 * i + ((c - 2 * (lane + 1)) & 7)][8 * lane + warp], mark);
      if (lane0) mbar_arrive(BAR(B_GFREE + w));
      if (lead) TSTAMP(w, 9);
      mbar_wait(BAR(B_P3F + 0), 0);
      wgmma_fence();
      #pragma unroll
      for (int ks = 0; ks < 7; ks++)
        wgmma_rt_n112(c3, uf[ks][0], uf[ks][1], uf[ks][2], uf[ks][3], mk_desc_ns(w3_off(0) + ks * 3584, 112), ks != 0);
      wgmma_commit();
      if (!early) { mbar_wait(BAR(B_OF), 0); load_o(); }
      const uint8_t* const obase = reinterpret_cast<const uint8_t*>(S->ofrag) + ((8 * i + 4 * kh) * 8 + warp) * 1792;
      ensure_o(of, obase + lane * 16, obase + 1536 + lane * 8, mark);
      #pragma unroll
      for (int hb = 0; hb < 2; hb++) {
        mbar_wait(BAR(B_P3F + 1 + hb), 0);
        wgmma_fence();
        #pragma unroll
        for (int ks = 0; ks < 7; ks++) {
          const int o = hb * 7 + ks;
          wgmma_rt_n112(c3, of[o][0], of[o][1], of[o][2], of[o][3], mk_desc_ns(w3_off(1 + hb) + ks * 3584, 112), 1);
        }
        wgmma_commit();
        wgmma_wait<1>();
        if (lead) mbar_arrive(BAR(B_WFREE + hb));
      }
      if (lead) TSTAMP(w, 10);
    }
    {
      uint4 t[3][7];
      #pragma unroll
      for (int b = 0; b < 3; b++) {
        mbar_wait(BAR(B_UF + 2 * b + w), 0);
        #pragma unroll
        for (int k = 0; k < 7; k++) t[b][k] = lds_v4(sb + ub_off(b) + w * ub_str(b) + v * 3584 + k * 512 + lane * 16);
        ensure_block(t[b], S->ufrag + ((8 * i + ((c + 2 * (b + 1)) & 7)) * 8 + warp) * 224 + lane, mark);
        if (lead) TSTAMP(w, 20 + b);
        mbar_wait(BAR(B_P3F + 3 + b), 0);
        wgmma_fence();
        #pragma unroll
        for (int ks = 0; ks < 7; ks++)
          wgmma_rt_n112(c3, t[b][ks].x, t[b][ks].y, t[b][ks].z, t[b][ks].w, mk_desc_ns(w3_off(3 + b) + ks * 3584, 112), 1);
        wgmma_commit();
        if (b == 0) { wgmma_wait<1>(); if (lead) mbar_arrive(BAR(B_RP2)); }
      }
    }
    wgmma_wait<0>();
    if (lead) TSTAMP(w, 11);
    {
      const uint32_t lb = sb + V_OFF + (uint32_t)w * (128 * 56);
      const uint32_t rbuf = mapa(lb, kh ^ 1), rbar = mapa(BAR(B_FX + w), kh ^ 1);
      #pragma unroll
      for (int k = 0; k < 3; k++) {
        const float* s = &c3[28 + 8 * k];
        st_async_v4(rbuf + k * 2048 + t128 * 16, pack_bf16(s[0], s[1]), pack_bf16(s[2], s[3]), pack_bf16(s[4], s[5]), pack_bf16(s[6], s[7]), rbar);
      }
      st_async_v2(rbuf + 3 * 2048 + t128 * 8, pack_bf16(c3[52], c3[53]), pack_bf16(c3[54], c3[55]), rbar);
      const uint32_t xa = sb + XO_OFF + (uint32_t)(16 * warp + (lm & 1) * 8 + lr) * 112;
      uint32_t xr[14];
      mbar_wait(BAR(B_HK), 1);
      #pragma unroll
      for (int np = 0; np < 3; np++) ldsm_x4(xa + (lm >> 1) * 16 + np * 32, xr[4 * np], xr[4 * np + 1], xr[4 * np + 2], xr[4 * np + 3]);
      ldsm_x2(xa + 96, xr[12], xr[13]);
      #pragma unroll
      for (int n = 0; n < 14; n++) { c3[2 * n] += bf_lo(xr[n]); c3[2 * n + 1] += bf_hi(xr[n]); }
      mbar_wait_cluster(BAR(B_FX + w), 0);
      uint32_t rv[14];
      #pragma unroll
      for (int k = 0; k < 3; k++) { const uint4 t = lds_v4(lb + k * 2048 + t128 * 16); rv[4 * k] = t.x; rv[4 * k + 1] = t.y; rv[4 * k + 2] = t.z; rv[4 * k + 3] = t.w; }
      { const uint2 t = lds_v2(lb + 3 * 2048 + t128 * 8); rv[12] = t.x; rv[13] = t.y; }
      #pragma unroll
      for (int n = 0; n < 14; n++) rv[n] = pack_bf16(c3[2 * n] + bf_lo(rv[n]), c3[2 * n + 1] + bf_hi(rv[n]));
      #pragma unroll
      for (int np = 0; np < 3; np++) stsm_x4(xa + (lm >> 1) * 16 + np * 32, rv[4 * np], rv[4 * np + 1], rv[4 * np + 2], rv[4 * np + 3]);
      stsm_x2(xa + 96, rv[12], rv[13]);
      fence_async_smem();
      __syncwarp();
      if (elect_one()) {
        tma_store_2d(&mOut, 56 * c, rowb, sb + XO_OFF + (uint32_t)warp * (16 * 112));
        asm volatile("cp.async.bulk.commit_group;" ::: "memory");
        asm volatile("cp.async.bulk.wait_group.read 0;" ::: "memory");
      }
      __syncwarp();
    }
    if (lead) TSTAMP(w, 12);
  }
}

typedef CUresult (*EncodeFn)(CUtensorMap*, CUtensorMapDataType, cuuint32_t, void*, const cuuint64_t*, const cuuint64_t*,
                             const cuuint32_t*, const cuuint32_t*, CUtensorMapInterleave, CUtensorMapSwizzle,
                             CUtensorMapL2promotion, CUtensorMapFloatOOBfill);

void make_map_2d(EncodeFn enc, CUtensorMap* m, const void* ptr, uint64_t inner, uint64_t outer, uint32_t box_inner, uint32_t box_outer,
                 CUtensorMapSwizzle swz) {
  cuuint64_t dims[2] = {inner, outer}; cuuint64_t strides[1] = {inner * 2};
  cuuint32_t box[2] = {box_inner, box_outer}; cuuint32_t es[2] = {1, 1};
  enc(m, CU_TENSOR_MAP_DATA_TYPE_BFLOAT16, 2, const_cast<void*>(ptr), dims, strides, box, es, CU_TENSOR_MAP_INTERLEAVE_NONE,
      swz, CU_TENSOR_MAP_L2_PROMOTION_L2_256B, CU_TENSOR_MAP_FLOAT_OOB_FILL_NONE);
}

void make_map_3d(EncodeFn enc, CUtensorMap* m, const void* ptr, uint64_t cols, uint64_t rows, uint32_t nblk) {
  cuuint64_t dims[3] = {64, rows, cols / 64}; cuuint64_t strides[2] = {cols * 2, 128};
  cuuint32_t box[3] = {64, 64, nblk}; cuuint32_t es[3] = {1, 1, 1};
  enc(m, CU_TENSOR_MAP_DATA_TYPE_BFLOAT16, 3, const_cast<void*>(ptr), dims, strides, box, es, CU_TENSOR_MAP_INTERLEAVE_NONE,
      CU_TENSOR_MAP_SWIZZLE_128B, CU_TENSOR_MAP_L2_PROMOTION_L2_256B, CU_TENSOR_MAP_FLOAT_OOB_FILL_NONE);
}

}

extern "C" void kernel_launch(void* const* d_in, const int* in_sizes, int n_in, void* d_out, int out_size) {
  (void)in_sizes; (void)n_in; (void)out_size;
  static EncodeFn enc = nullptr;
  static void* scratch = nullptr;
  if (!enc) {
    void* fn = nullptr; cudaDriverEntryPointQueryResult st;
    cudaGetDriverEntryPoint("cuTensorMapEncodeTiled", &fn, cudaEnableDefault, &st);
    enc = (EncodeFn)fn;
    cudaGetSymbolAddress(&scratch, g_scratch);
    cudaFuncSetAttribute(fused_kernel, cudaFuncAttributeMaxDynamicSharedMemorySize, SMEM_BYTES);
  }
  CUtensorMap mX, mWin, mWsp, mXr, mOut;
  make_map_3d(enc, &mX, d_in[0], 448, 2048, 7);
  make_map_3d(enc, &mWin, d_in[4], 1792, 448, 2);
  make_map_2d(enc, &mWsp, d_in[5], 2048, 2048, 64, 128, CU_TENSOR_MAP_SWIZZLE_128B);
  make_map_2d(enc, &mXr, d_in[0], 448, 2048, 56, 128, CU_TENSOR_MAP_SWIZZLE_NONE);
  make_map_2d(enc, &mOut, d_out, 448, 2048, 56, 16, CU_TENSOR_MAP_SWIZZLE_NONE);
  Params p;
  p.x = (const __nv_bfloat16*)d_in[0]; p.wqkv = (const __nv_bfloat16*)d_in[1]; p.win = (const __nv_bfloat16*)d_in[4];
  p.wsp = (const __nv_bfloat16*)d_in[5]; p.bsp = (const __nv_bfloat16*)d_in[6];
  p.wo = (const __nv_bfloat16*)d_in[2]; p.wout = (const __nv_bfloat16*)d_in[7]; p.out = (__nv_bfloat16*)d_out; p.S = (Scratch*)scratch; p.zero = 0;
  cudaLaunchConfig_t cfg = {};
  cfg.gridDim = dim3(128 + NSVC); cfg.blockDim = dim3(384); cfg.dynamicSmemBytes = SMEM_BYTES; cfg.stream = cudaStreamPerThread;
  cudaLaunchAttribute at[1];
  at[0].id = cudaLaunchAttributeClusterDimension; at[0].val.clusterDim.x = 2; at[0].val.clusterDim.y = 1; at[0].val.clusterDim.z = 1;
  cfg.attrs = at; cfg.numAttrs = 1;
  cudaLaunchKernelEx(&cfg, fused_kernel, mX, mWin, mWsp, mXr, mOut, p);
}
```
